```python
import torch

def _softmax(x, axis=-1):
    return torch.softmax(x, dim=axis)
def _gelu(x):
    return torch.nn.functional.gelu(x, approximate="tanh")
def _silu(x):
    return torch.nn.functional.silu(x)
def _sigmoid(x):
    return torch.sigmoid(x)
def _layernorm(x, axis=-1, eps=1e-5):
    m = x.mean(dim=axis, keepdim=True)
    v = x.var(dim=axis, keepdim=True, unbiased=False)
    return (x - m) / torch.sqrt(v + eps)
def _scatter_add(tgt, idx, src, axis=0):
    return tgt.clone().index_add_(axis, idx, src)
def _segment_sum(src, seg, n):
    out = torch.zeros((n,) + src.shape[1:], dtype=src.dtype)
    return out.index_add_(0, seg, src)
def _pad(x, pw):
    flat = tuple(v for pair in reversed(pw) for v in pair)
    return torch.nn.functional.pad(x, flat)

kernel_name = 'gated_mix__sliding_block_cached__dense_activation_mish__decode'

def setup_inputs():

    _w = (lambda a: (lambda t: t.to(torch.bfloat16) if t.is_floating_point() else t)(torch.as_tensor(a)))
    def _A_setup():
        B, Sq, D = 4, 1, 512
        Hq, Hkv, Sk, Dh = 32, 8, 4096, 128
        assert Hq % Hkv == 0, (Hq, Hkv)
        return {
            "x": _w((lambda *s: torch.randn(*s, dtype=torch.bfloat16) * 0.05)(B, Sq, D)),
            "k_cache": _w((lambda *s: torch.randn(*s, dtype=torch.bfloat16) * 6.4)(B, Hkv, Sk, Dh)),
            "v_cache": _w((lambda *s: torch.randn(*s, dtype=torch.bfloat16) * 0.1)(B, Hkv, Sk, Dh)),
            "wq": _w((lambda *s: torch.randn(*s, dtype=torch.bfloat16) * 6.4)(D, Hq * Dh) * (D ** -0.5)),
            "wo": _w((lambda *s: torch.randn(*s, dtype=torch.bfloat16) * 0.1)(Hq * Dh, D) * ((Hq * Dh) ** -0.5)),
        }
    _A_in = _A_setup()

    def _B_setup():
        B, S, D, F = 4, 1, 512, 1792
        return {
            "x": _w((lambda *s: torch.randn(*s, dtype=torch.bfloat16) * 0.05)(B, S, D)),
            "w1": _w((lambda *s: torch.randn(*s, dtype=torch.bfloat16) * 3.2)(D, F) * (D ** -0.5)),
            "b1": _w((lambda *s: torch.randn(*s, dtype=torch.bfloat16) * 0.1)(F)),
            "w2": _w((lambda *s: torch.randn(*s, dtype=torch.bfloat16) * 0.1)(F, D) * (F ** -0.5)),
        }
    _B_in = _B_setup()

    return {
        "A_x": _A_in["x"],
        "A_k_cache": _A_in["k_cache"],
        "A_v_cache": _A_in["v_cache"],
        "A_wq": _A_in["wq"],
        "A_wo": _A_in["wo"],
        "B_x": _B_in["x"],
        "B_w1": _B_in["w1"],
        "B_b1": _B_in["b1"],
        "B_w2": _B_in["w2"],
        "gate_w": _w((lambda *s: torch.randn(*s, dtype=torch.bfloat16) * 0.05)(512) * 16.0),
    }

def reference(A_x, A_k_cache, A_v_cache, A_wq, A_wo, B_x, B_w1, B_b1, B_w2, gate_w):
    def _A_ref(x, k_cache, v_cache, wq, wo):
        B, Sq, D = x.shape
        Hq, Dh = 32, 128
        Hkv, Sk = k_cache.shape[1], k_cache.shape[2]
        W = min(4096, max(256, Sk // 4))
        rep = Hq // Hkv
        q = (lambda x, *d: x.permute(*d))((x @ wq).reshape(B, Sq, Hq, Dh), 0, 2, 1, 3)
        k = (lambda x, n, axis: torch.repeat_interleave(x, n, dim=axis))(k_cache[:, :, Sk - W:, :], rep, axis=1)
        v = (lambda x, n, axis: torch.repeat_interleave(x, n, dim=axis))(v_cache[:, :, Sk - W:, :], rep, axis=1)
        scores = torch.einsum("bhqd,bhkd->bhqk", q, k) * (Dh ** -0.5)
        p = _softmax(scores, axis=-1)
        o = torch.einsum("bhqk,bhkd->bhqd", p, v)
        return (lambda x, *d: x.permute(*d))(o, 0, 2, 1, 3).reshape(B, Sq, Hq * Dh) @ wo

    def _B_ref(x, w1, b1, w2):
        h = torch.einsum("bsd,df->bsf", x, w1) + b1
        sp = torch.log1p(torch.exp(-torch.abs(h))) + torch.where(h > 0, h, torch.zeros_like(h))
        act = h * torch.tanh(sp)
        return torch.einsum("bsf,fd->bsd", act, w2)

    x = A_x
    g = _sigmoid((x * gate_w).sum(-1, keepdims=True))
    a = _A_ref(x, A_k_cache, A_v_cache, A_wq, A_wo)
    b = _B_ref(x, B_w1, B_b1, B_w2)
    return g * a + (1 - g) * b
```

```cpp
#include <cuda_runtime.h>
#include <cuda_bf16.h>
#include <cuda.h>
#include <stdint.h>

namespace {

constexpr int NCTA = 128;
constexpr int NFFN = 112;
constexpr int NTHREADS = 288;
#define PACE_LEAD 4
#define PACE_T0 0
#define PACE_NS 355
#define WINDOW 7
#define EARLY_PREFETCH
#define O_AFTER_WO 1
#define EPOCH_MODE 0
#define Q_AFTER_K 1
#define WINDOW0 4

constexpr int D_MODEL = 512, HQ = 32, HKV = 8, SK = 4096, WIN = 1024, DH = 128, FF = 1792;

constexpr int OFF_A = 0;
constexpr int OFF_K = 32768;
constexpr int OFF_V = OFF_K + 65536;
constexpr int OFF_W1 = OFF_V + 65536;
constexpr int OFF_W2 = OFF_W1 + 16384;
constexpr int OFF_REDQ = OFF_W2 + 16384;
constexpr int OFF_XS = OFF_REDQ + 4096;
constexpr int OFF_QS = OFF_XS + 4 * 1040;
constexpr int OFF_PS = OFF_QS + 4 * 272;
constexpr int OFF_OS = OFF_PS + 8 * 528;
constexpr int OFF_AS = OFF_OS + 4 * 272;
constexpr int OFF_WMAX = OFF_AS + 4 * 144;
constexpr int OFF_WSUM = OFF_WMAX + 128;
constexpr int OFF_GATE = OFF_WSUM + 128;
constexpr int OFF_EPOCH = OFF_GATE + 16;
constexpr int OFF_BAR = OFF_EPOCH + 16;
constexpr int C_WQ = 0, C_W1 = 4, C_K = 6, C_V = 14, C_WO = 22, C_W2 = 26, NCHUNK = 28;
constexpr int SMEM_BYTES = OFF_BAR + (NCHUNK + 1) * 8;
static_assert(OFF_BAR % 8 == 0, "align");
static_assert(SMEM_BYTES <= 232448, "smem");

struct alignas(64) Params {
    const __nv_bfloat16* x;
    const __nv_bfloat16* b1;
    const __nv_bfloat16* gate_w;
    __nv_bfloat16* out;
    const char* wq;
    float* scratch;
    alignas(64) CUtensorMap m_wq;
    alignas(64) CUtensorMap m_w1;
    alignas(64) CUtensorMap m_k;
    alignas(64) CUtensorMap m_v;
    alignas(64) CUtensorMap m_wo;
    alignas(64) CUtensorMap m_w2;
};

constexpr int SC_EPOCH = 0;
constexpr int SC_Q = SC_EPOCH + NCTA * 32;
constexpr int SC_H = SC_Q + 4 * HQ * DH;
constexpr int SC_ST = SC_H + 28 * 4 * 64 * 4;
constexpr int SC_O = SC_ST + HQ * 4 * 4 * 2;
constexpr int SC_P = SC_O + HQ * 4 * 4 * DH;
constexpr int SC_TOTAL = SC_P + NCTA * 32 * 16;
__device__ __align__(128) float g_scratch[SC_TOTAL];
#define TS(k)
#define TSW(w_, k)
#define TS_DUMP()

__device__ __forceinline__ uint32_t smem_u32(const void* p) { return (uint32_t)__cvta_generic_to_shared(p); }
__device__ __forceinline__ void mbar_init(uint32_t bar, uint32_t cnt) {
    asm volatile("mbarrier.init.shared::cta.b64 [%0], %1;" :: "r"(bar), "r"(cnt) : "memory");
}
__device__ __forceinline__ void mbar_expect_tx(uint32_t bar, uint32_t bytes) {
    asm volatile("mbarrier.arrive.expect_tx.shared::cta.b64 _, [%0], %1;" :: "r"(bar), "r"(bytes) : "memory");
}
__device__ __forceinline__ void mbar_arrive(uint32_t bar) {
    asm volatile("mbarrier.arrive.shared::cta.b64 _, [%0];" :: "r"(bar) : "memory");
}
__device__ __forceinline__ bool mbar_try(uint32_t bar, uint32_t parity) {
    uint32_t ok;
    asm volatile("{\n.reg .pred p;\nmbarrier.try_wait.parity.shared::cta.b64 p, [%1], %2;\nselp.u32 %0, 1, 0, p;\n}"
                 : "=r"(ok) : "r"(bar), "r"(parity) : "memory");
    return ok;
}
constexpr int SPIN_LIMIT = 1 << 22;
__device__ __forceinline__ void mbar_wait(uint32_t bar) {
    int it = 0;
    while (!mbar_try(bar, 0)) { if (++it > SPIN_LIMIT) __trap(); }
}
__device__ __forceinline__ void mbar_wait_warp(uint32_t bar) { mbar_wait(bar); __syncwarp(); }
__device__ __forceinline__ void tma2d(uint32_t dst, const CUtensorMap* m, int c0, int c1, uint32_t bar, uint64_t pol) {
    asm volatile("cp.async.bulk.tensor.2d.shared::cluster.global.mbarrier::complete_tx::bytes.L2::cache_hint"
                 " [%0], [%1, {%3, %4}], [%2], %5;"
                 :: "r"(dst), "l"(m), "r"(bar), "r"(c0), "r"(c1), "l"(pol) : "memory");
}
__device__ __forceinline__ void tma3d(uint32_t dst, const CUtensorMap* m, int c0, int c1, int c2, uint32_t bar, uint64_t pol) {
    asm volatile("cp.async.bulk.tensor.3d.shared::cluster.global.mbarrier::complete_tx::bytes.L2::cache_hint"
                 " [%0], [%1, {%3, %4, %5}], [%2], %6;"
                 :: "r"(dst), "l"(m), "r"(bar), "r"(c0), "r"(c1), "r"(c2), "l"(pol) : "memory");
}
__device__ __forceinline__ void ldsm4(uint32_t (&r)[4], uint32_t a) {
    asm volatile("ldmatrix.sync.aligned.m8n8.x4.shared.b16 {%0,%1,%2,%3}, [%4];"
                 : "=r"(r[0]), "=r"(r[1]), "=r"(r[2]), "=r"(r[3]) : "r"(a) : "memory");
}
__device__ __forceinline__ void ldsm4t(uint32_t (&r)[4], uint32_t a) {
    asm volatile("ldmatrix.sync.aligned.m8n8.x4.trans.shared.b16 {%0,%1,%2,%3}, [%4];"
                 : "=r"(r[0]), "=r"(r[1]), "=r"(r[2]), "=r"(r[3]) : "r"(a) : "memory");
}
__device__ __forceinline__ void stsm4t(uint32_t a, uint32_t r0, uint32_t r1, uint32_t r2, uint32_t r3) {
    asm volatile("stmatrix.sync.aligned.m8n8.x4.trans.shared.b16 [%0], {%1,%2,%3,%4};"
                 :: "r"(a), "r"(r0), "r"(r1), "r"(r2), "r"(r3) : "memory");
}
__device__ __forceinline__ void mma16816(float (&c)[4], const uint32_t (&a)[4], uint32_t b0, uint32_t b1) {
    asm volatile("mma.sync.aligned.m16n8k16.row.col.f32.bf16.bf16.f32 {%0,%1,%2,%3}, {%4,%5,%6,%7}, {%8,%9}, {%0,%1,%2,%3};"
                 : "+f"(c[0]), "+f"(c[1]), "+f"(c[2]), "+f"(c[3])
                 : "r"(a[0]), "r"(a[1]), "r"(a[2]), "r"(a[3]), "r"(b0), "r"(b1));
}
__device__ __forceinline__ uint32_t pack_bf16(float lo, float hi) {
    uint32_t r;
    asm("cvt.rn.bf16x2.f32 %0, %1, %2;" : "=r"(r) : "f"(hi), "f"(lo));
    return r;
}
__device__ __forceinline__ void csync() { asm volatile("bar.sync 1, 256;" ::: "memory"); }

__device__ __forceinline__ uint32_t tagw(float v, uint32_t tag) { return (__float_as_uint(v) & ~3u) | tag; }
__device__ __forceinline__ void st_mail(float* p, uint32_t v) {
    asm volatile("st.relaxed.gpu.global.b32 [%0], %1;" :: "l"(p), "r"(v) : "memory");
}
__device__ __forceinline__ void st_mail2(float* p, uint32_t v0, uint32_t v1) {
    asm volatile("st.relaxed.gpu.global.v2.b32 [%0], {%1, %2};" :: "l"(p), "r"(v0), "r"(v1) : "memory");
}
__device__ __forceinline__ uint4 ld_mail4(const float* p) {
    uint4 v;
    asm volatile("ld.relaxed.gpu.global.v4.b32 {%0,%1,%2,%3}, [%4];" : "=r"(v.x), "=r"(v.y), "=r"(v.z), "=r"(v.w) : "l"(p) : "memory");
    return v;
}
__device__ __forceinline__ bool tag_ok(const uint4& v, uint32_t tag) {
    return (((v.x ^ tag) | (v.y ^ tag) | (v.z ^ tag) | (v.w ^ tag)) & 3u) == 0;
}
template <int N>
__device__ __forceinline__ void poll_mail(uint4 (&v)[N], const float* p, int stride, uint32_t tag) {
    int it = 0;
    while (true) {
        bool ok = true;
#pragma unroll
        for (int i = 0; i < N; i++) v[i] = ld_mail4(p + i * stride);
#pragma unroll
        for (int i = 0; i < N; i++) ok = ok && tag_ok(v[i], tag);
        if (__all_sync(0xffffffffu, ok)) break;
        if (++it > SPIN_LIMIT) __trap();
    }
}
__device__ __forceinline__ float u2f(uint32_t u) { return __uint_as_float(u); }
__device__ __forceinline__ uint64_t gtime() { uint64_t t; asm volatile("mov.u64 %0, %globaltimer;" : "=l"(t)); return t; }
__device__ __forceinline__ float mish(float h) {
    const float e = __expf(fminf(h, 30.f));
    const float n = e * (e + 2.f);
    return h * __fdividef(n, n + 2.f);
}

__global__ void __launch_bounds__(NTHREADS, 1)
gated_mix_kernel(const __grid_constant__ Params prm) {
    extern __shared__ __align__(1024) unsigned char smem[];
    const uint32_t sb = smem_u32(smem);
    const int warp = threadIdx.x >> 5, lane = threadIdx.x & 31;
    const int cta = blockIdx.x;
    const uint32_t bar0 = sb + OFF_BAR;

    const bool ffn = cta < NFFN;
    if (__builtin_expect(warp == 8, 1)) {
        TS(0);
        uint64_t pol;
        asm volatile("createpolicy.fractional.L2::evict_first.b64 %0, 1.0;" : "=l"(pol));
        const int kvrow = (cta >> 2) * SK + (SK - WIN) + (cta & 3) * 256;
        auto issue = [&](int j) {
            const uint32_t bar = bar0 + 8 * j;
            if (j < 4) {
                mbar_expect_tx(bar, 8192);
                tma2d(sb + OFF_A + j * 8192, &prm.m_wq, cta * 32, j * 128, bar, pol);
            } else if (j >= C_K && j < C_K + 8) {
                mbar_expect_tx(bar, 8192);
                tma3d(sb + OFF_K + (j - C_K) * 8192, &prm.m_k, 0, kvrow + (j - C_K) * 32, 0, bar, pol);
            } else if (j >= C_V && j < C_V + 8) {
                mbar_expect_tx(bar, 8192);
                tma3d(sb + OFF_V + (j - C_V) * 8192, &prm.m_v, 0, kvrow + (j - C_V) * 32, 0, bar, pol);
            } else if (j >= C_W1 && j < C_W1 + 2) {
                if (ffn) { mbar_expect_tx(bar, 8192); tma2d(sb + OFF_W1 + (j - C_W1) * 8192, &prm.m_w1, (cta >> 2) * 64, (cta & 3) * 128 + (j - C_W1) * 64, bar, pol); }
                else mbar_arrive(bar);
            } else if (j < C_W2) {
                mbar_expect_tx(bar, 8192);
                tma3d(sb + OFF_A + (j - C_WO) * 8192, &prm.m_wo, 0, (cta >> 2) * 128 + (j - C_WO) * 32, (cta & 3) * 2, bar, pol);
            } else {
                if (ffn) { mbar_expect_tx(bar, 8192); tma3d(sb + OFF_W2 + (j - C_W2) * 8192, &prm.m_w2, 0, (cta >> 2) * 64 + (j - C_W2) * 32, (cta & 3) * 2, bar, pol); }
                else mbar_arrive(bar);
            }
        };
        if (lane == 0) {
            asm volatile("cp.async.bulk.prefetch.L2.global [%0], %1;" :: "l"(prm.wq + (size_t)cta * 32768), "r"(32768) : "memory");
#pragma unroll
            for (int j = 0; j < 4; j++) { mbar_init(bar0 + 8 * j, 1); if (j < WINDOW0) issue(j); TS(24 + j); }
            asm volatile("prefetch.tensormap [%0];" :: "l"(&prm.m_w1) : "memory");
            asm volatile("prefetch.tensormap [%0];" :: "l"(&prm.m_k) : "memory");
            TS(1);
        }
        __syncwarp();
        asm volatile("bar.sync 2, 288;" ::: "memory");
        if (lane == 0) {
#pragma unroll
            for (int j = WINDOW0; j < WINDOW; j++) issue(j);
            asm volatile("prefetch.tensormap [%0];" :: "l"(&prm.m_v) : "memory");
            asm volatile("prefetch.tensormap [%0];" :: "l"(&prm.m_wo) : "memory");
            asm volatile("prefetch.tensormap [%0];" :: "l"(&prm.m_w2) : "memory");
            const uint64_t t0 = gtime();
#pragma unroll
            for (int j = WINDOW; j < NCHUNK; j++) {
                mbar_wait(bar0 + 8 * (j - WINDOW));
                TS(32 + j - WINDOW);
                if (j == C_WO) mbar_wait(bar0 + 8 * NCHUNK);
                { int it = 0; while (gtime() < t0 + (uint64_t)((j - PACE_LEAD) * PACE_NS) + PACE_T0 && ++it < SPIN_LIMIT) {} }
                issue(j);
            }
        }
        TS_DUMP();
        return;
    }

    const int g = lane >> 2, t = lane & 3;
    const int j8 = lane >> 3, i8 = lane & 7;
    const int hi = t >> 1, bp = 2 * (t & 1);
    const int tid = threadIdx.x;
    float* const scr = prm.scratch;
    float* const g_q = scr + SC_Q;
    float* const g_h = scr + SC_H;
    float* const g_st = scr + SC_ST;
    float* const g_o = scr + SC_O;
    float* const g_p = scr + SC_P;
    unsigned int* const g_epoch = reinterpret_cast<unsigned int*>(scr) + SC_EPOCH;
    const int ab = cta >> 5, ahkv = (cta >> 2) & 7, as = cta & 3;
    const int ph = cta >> 2, pc = cta & 3;
    uint4 xv0, xv1;
    unsigned int epoch = 0;
    float* const q_slot = g_q + ((tid & 3) * HQ + ph) * DH + 32 * pc + ((tid >> 2) & 31);
    if (warp < 4) {
        xv0 = __ldg(reinterpret_cast<const uint4*>(prm.x) + tid);
        xv1 = __ldg(reinterpret_cast<const uint4*>(prm.x) + 128 + tid);
        if (tid == 0) asm volatile("ld.relaxed.gpu.global.u32 %0, [%1];" : "=r"(epoch) : "l"(&g_epoch[cta * 32]) : "memory");
        st_mail(q_slot, 0u);
    } else {
        if (lane == 0) {
#pragma unroll
            for (int j = 0; j < 6; j++) mbar_init(bar0 + 8 * (4 + 6 * (warp - 4) + j), 1);
            if (warp == 4) mbar_init(bar0 + 8 * NCHUNK, 8);
            asm volatile("fence.mbarrier_init.release.cluster;" ::: "memory");
        }
        __syncwarp();
    }
    TS(22);
    asm volatile("bar.sync 2, 288;" ::: "memory");

    float* const h_slot = g_h + cta * 256 + (16 * (warp & 3) + g + 8 * hi) * 4 + bp;
    float* const st_slot = g_st + (((4 * ahkv + (lane & 3)) * 4 + ab) * 4 + as) * 2;
    float* const o_slot = g_o + (((4 * ahkv + bp) * 4 + ab) * 4 + as) * DH + 16 * warp + g + 8 * hi;
    float* const p_slot = g_p + ((32 * pc + ((32 * (warp & 3) + g + 8 * hi) >> 2)) * 32 + ph) * 16 + (g & 3) * 4 + bp;

    TS(23);
    if (warp < 4) {
        *reinterpret_cast<uint4*>(smem + OFF_XS + (tid >> 6) * 1040 + (tid & 63) * 16) = xv0;
        *reinterpret_cast<uint4*>(smem + OFF_XS + (2 + (tid >> 6)) * 1040 + (tid & 63) * 16) = xv1;
    }
    TS(24);
    csync();
    uint32_t xq[2][4];
#pragma unroll
    for (int u = 0; u < 2; u++) ldsm4(xq[u], sb + OFF_XS + (i8 & 3) * 1040 + (64 * warp + 32 * u + 8 * j8) * 2);
    TS(0);
    uint32_t tag;

    {
        float aq[2][4] = {};
        mbar_wait_warp(bar0 + 8 * (C_WQ + (warp >> 1)));
        TS(2);
        const uint32_t base = sb + OFF_A + (warp >> 1) * 8192;
#pragma unroll
        for (int ks = 0; ks < 4; ks++) {
            const int row = 64 * (warp & 1) + 16 * ks + i8 + 8 * (j8 >> 1);
#pragma unroll
            for (int mt = 0; mt < 2; mt++) {
                uint32_t a[4];
                ldsm4t(a, base + row * 64 + (((2 * mt + (j8 & 1)) ^ ((row >> 1) & 3)) << 4));
                mma16816(aq[mt], a, xq[ks >> 1][2 * (ks & 1)], xq[ks >> 1][2 * (ks & 1) + 1]);
            }
        }
        TS(12);
        __syncwarp();
        if (lane == 0) mbar_arrive(bar0 + 8 * NCHUNK);
        float* redq = reinterpret_cast<float*>(smem + OFF_REDQ);
        {
            const float v0 = hi ? aq[1][0] : aq[0][0], v1 = hi ? aq[1][1] : aq[0][1];
            const float v2 = hi ? aq[1][2] : aq[0][2], v3 = hi ? aq[1][3] : aq[0][3];
            *reinterpret_cast<float2*>(redq + (warp * 32 + 16 * hi + g) * 4 + bp) = make_float2(v0, v1);
            *reinterpret_cast<float2*>(redq + (warp * 32 + 16 * hi + g + 8) * 4 + bp) = make_float2(v2, v3);
        }
        if (tid == 0) *reinterpret_cast<unsigned int*>(smem + OFF_EPOCH) = epoch;
        TS(25);
        csync();
        epoch = *reinterpret_cast<const unsigned int*>(smem + OFF_EPOCH);
        tag = 1u + (epoch & 1u);
        if (tid < 128) {
            float s = 0.f;
#pragma unroll
            for (int w = 0; w < 8; w++) s += redq[w * 128 + tid];
            st_mail(q_slot, (pack_bf16(0.f, s) & 0xffff0000u) | tag);
        }
        TS(3);
    }

    if (ffn && warp >= 4) st_mail2(h_slot, 0u, 0u);
    if (warp == 0 && lane < 4) st_mail2(st_slot, 0u, 0u);
    st_mail(o_slot, 0u);
    st_mail(o_slot + 16 * DH, 0u);
    if (warp >= 4) { st_mail2(p_slot, 0u, 0u); st_mail2(p_slot + 4 * 32 * 16, 0u, 0u); }

    auto h_partial = [&]() {
        uint32_t xh[4][4];
#pragma unroll
        for (int u = 0; u < 4; u++) ldsm4(xh[u], sb + OFF_XS + (i8 & 3) * 1040 + (128 * pc + 32 * u + 8 * j8) * 2);
        float h0[4] = {}, h1[4] = {};
#pragma unroll
        for (int c = 0; c < 2; c++) {
            mbar_wait_warp(bar0 + 8 * (C_W1 + c));
#pragma unroll
            for (int ks = 0; ks < 4; ks++) {
                const int row = 16 * ks + i8 + 8 * (j8 >> 1);
                uint32_t a[4];
                ldsm4t(a, sb + OFF_W1 + c * 8192 + row * 128 + (((2 * (warp & 3) + (j8 & 1)) ^ (row & 7)) << 4));
                const int u = 2 * c + (ks >> 1);
                if (ks & 1) mma16816(h1, a, xh[u][2], xh[u][3]);
                else        mma16816(h0, a, xh[u][0], xh[u][1]);
            }
        }
        st_mail2(h_slot, tagw(hi ? h0[2] + h1[2] : h0[0] + h1[0], tag), tagw(hi ? h0[3] + h1[3] : h0[1] + h1[1], tag));
        TS(19);
    };
    auto activation = [&]() {
        const int col = (warp - 4) * 32 + lane;
        const float bias = __bfloat162float(prm.b1[ph * 64 + col]);
        uint4 v[4];
        poll_mail<4>(v, g_h + (ph * 4 * 64 + col) * 4, 256, tag);
        TS(20);
        const float hv[4] = {(u2f(v[0].x) + u2f(v[1].x)) + (u2f(v[2].x) + u2f(v[3].x)) + bias,
                             (u2f(v[0].y) + u2f(v[1].y)) + (u2f(v[2].y) + u2f(v[3].y)) + bias,
                             (u2f(v[0].z) + u2f(v[1].z)) + (u2f(v[2].z) + u2f(v[3].z)) + bias,
                             (u2f(v[0].w) + u2f(v[1].w)) + (u2f(v[2].w) + u2f(v[3].w)) + bias};
#pragma unroll
        for (int b = 0; b < 4; b++)
            *reinterpret_cast<__nv_bfloat16*>(smem + OFF_AS + b * 144 + col * 2) = __float2bfloat16(mish(hv[b]));
    };

    if (warp < 4) {
        uint4 v[1];
        mbar_wait_warp(bar0 + 8 * (C_K + Q_AFTER_K));
        poll_mail<1>(v, g_q + (ab * HQ + 4 * ahkv + warp) * DH + 4 * lane, 0, tag);
        const uint32_t p0 = (v[0].x >> 16) | (v[0].y & 0xffff0000u), p1 = (v[0].z >> 16) | (v[0].w & 0xffff0000u);
        *reinterpret_cast<uint2*>(smem + OFF_QS + warp * 272 + lane * 8) = make_uint2(p0, p1);
        TS(21);
    } else {
        const int b = warp - 4;
        const uint4* gr = reinterpret_cast<const uint4*>(prm.gate_w);
        const uint4 gv0 = __ldg(gr + lane), gv1 = __ldg(gr + 32 + lane);
        if (ffn) h_partial();
        float s = 0.f;
#pragma unroll
        for (int u = 0; u < 2; u++) {
            const uint4 xx = *reinterpret_cast<const uint4*>(smem + OFF_XS + b * 1040 + (u * 32 + lane) * 16), gv = u ? gv1 : gv0;
            const uint32_t xa[4] = {xx.x, xx.y, xx.z, xx.w}, ga[4] = {gv.x, gv.y, gv.z, gv.w};
#pragma unroll
            for (int e = 0; e < 4; e++) {
                s = fmaf(u2f(xa[e] << 16), u2f(ga[e] << 16), s);
                s = fmaf(u2f(xa[e] & 0xffff0000u), u2f(ga[e] & 0xffff0000u), s);
            }
        }
#pragma unroll
        for (int o = 16; o > 0; o >>= 1) s += __shfl_xor_sync(0xffffffffu, s, o);
        if (lane == 0) reinterpret_cast<float*>(smem + OFF_GATE)[b] = 1.f / (1.f + __expf(-s));
    }
    csync();

    constexpr float SC = 0.08838834764831845f * 1.4426950408889634f;
    float* wmax = reinterpret_cast<float*>(smem + OFF_WMAX);
    float* wsum = reinterpret_cast<float*>(smem + OFF_WSUM);
    {
        uint32_t qf[4][4];
#pragma unroll
        for (int u = 0; u < 4; u++) ldsm4(qf[u], sb + OFF_QS + (i8 & 3) * 272 + (32 * u + 8 * j8) * 2);
        TS(4);
        float s[2][4] = {};
        mbar_wait_warp(bar0 + 8 * (C_K + warp));
        TS(5);
        const uint32_t base = sb + OFF_K + warp * 8192;
#pragma unroll
        for (int ks = 0; ks < 8; ks++) {
#pragma unroll
            for (int mt = 0; mt < 2; mt++) {
                const int row = 16 * mt + i8 + 8 * (j8 & 1);
                uint32_t a[4];
                ldsm4(a, base + (ks >> 2) * 4096 + row * 128 + (((2 * (ks & 3) + (j8 >> 1)) ^ (row & 7)) << 4));
                mma16816(s[mt], a, qf[ks >> 1][2 * (ks & 1)], qf[ks >> 1][2 * (ks & 1) + 1]);
            }
        }
        float m0 = fmaxf(fmaxf(s[0][0], s[0][2]), fmaxf(s[1][0], s[1][2]));
        float m1 = fmaxf(fmaxf(s[0][1], s[0][3]), fmaxf(s[1][1], s[1][3]));
#pragma unroll
        for (int o = 4; o < 32; o <<= 1) {
            m0 = fmaxf(m0, __shfl_xor_sync(0xffffffffu, m0, o));
            m1 = fmaxf(m1, __shfl_xor_sync(0xffffffffu, m1, o));
        }
        if (lane < 2) *reinterpret_cast<float2*>(wmax + warp * 4 + 2 * lane) = make_float2(m0, m1);
        csync();
        m0 = -INFINITY; m1 = -INFINITY;
#pragma unroll
        for (int w = 0; w < 8; w++) {
            const float2 mm = *reinterpret_cast<const float2*>(wmax + w * 4 + bp);
            m0 = fmaxf(m0, mm.x); m1 = fmaxf(m1, mm.y);
        }
        float p[2][4];
#pragma unroll
        for (int mt = 0; mt < 2; mt++) {
            p[mt][0] = exp2f((s[mt][0] - m0) * SC); p[mt][1] = exp2f((s[mt][1] - m1) * SC);
            p[mt][2] = exp2f((s[mt][2] - m0) * SC); p[mt][3] = exp2f((s[mt][3] - m1) * SC);
        }
        float l0 = (p[0][0] + p[0][2]) + (p[1][0] + p[1][2]), l1 = (p[0][1] + p[0][3]) + (p[1][1] + p[1][3]);
#pragma unroll
        for (int o = 4; o < 32; o <<= 1) {
            l0 += __shfl_xor_sync(0xffffffffu, l0, o);
            l1 += __shfl_xor_sync(0xffffffffu, l1, o);
        }
        if (lane < 2) *reinterpret_cast<float2*>(wsum + warp * 4 + 2 * lane) = make_float2(l0, l1);
        stsm4t(sb + OFF_PS + i8 * 528 + (32 * warp + 8 * j8) * 2,
               pack_bf16(p[0][0], p[0][1]), pack_bf16(p[0][2], p[0][3]),
               pack_bf16(p[1][0], p[1][1]), pack_bf16(p[1][2], p[1][3]));
        csync();
        if (warp == 0 && lane < 4) {
            float l = 0.f, m = -INFINITY;
#pragma unroll
            for (int w = 0; w < 8; w++) { l += wsum[w * 4 + lane]; m = fmaxf(m, wmax[w * 4 + lane]); }
            st_mail2(st_slot, tagw(m, tag), tagw(l, tag));
        }
    }
    TS(6);
    if (ffn && (warp == 4 || warp == 5)) activation();

    uint4 sv0 = make_uint4(0, 0, 0, 0), sv1 = sv0;
    const float* const st_src = g_st + (ph * 4 + (warp & 3)) * 8;
    {
        float o0[4] = {}, o1[4] = {};
#pragma unroll
        for (int c = 0; c < 8; c++) {
            if (c == 5 && warp < 4) { sv0 = ld_mail4(st_src); sv1 = ld_mail4(st_src + 4); }
            uint32_t pf[4];
            ldsm4(pf, sb + OFF_PS + i8 * 528 + (32 * c + 8 * j8) * 2);
            mbar_wait_warp(bar0 + 8 * (C_V + c));
            const uint32_t base = sb + OFF_V + c * 8192 + (warp >> 2) * 4096;
#pragma unroll
            for (int ks = 0; ks < 2; ks++) {
                const int row = 16 * ks + i8 + 8 * (j8 >> 1);
                uint32_t a[4];
                ldsm4t(a, base + row * 128 + (((2 * (warp & 3) + (j8 & 1)) ^ (row & 7)) << 4));
                if (ks & 1) mma16816(o1, a, pf[2], pf[3]);
                else        mma16816(o0, a, pf[0], pf[1]);
            }
        }
        TS(18);
        const float v0 = hi ? o0[2] + o1[2] : o0[0] + o1[0];
        const float v1 = hi ? o0[3] + o1[3] : o0[1] + o1[1];
        st_mail(o_slot, tagw(v0, tag));
        st_mail(o_slot + 16 * DH, tagw(v1, tag));
    }
    TS(7);

    if (warp < 4) {
        uint4 v[4];
        const float* po = g_o + (ph * 4 + warp) * 4 * DH + 4 * lane;
        float w0 = 0.f, w1 = 0.f, w2 = 0.f, w3 = 0.f;
        mbar_wait_warp(bar0 + 8 * (C_WO + O_AFTER_WO));
        bool sok = false, ok[4] = {false, false, false, false};
        int it = 0;
        while (true) {
#pragma unroll
            for (int i = 0; i < 4; i++) if (!ok[i]) v[i] = ld_mail4(po + i * DH);
            if (!sok) {
                sok = tag_ok(sv0, tag) && tag_ok(sv1, tag);
                if (sok) {
                    const float m0 = u2f(sv0.x), m1 = u2f(sv0.z), m2 = u2f(sv1.x), m3 = u2f(sv1.z);
                    const float mm = fmaxf(fmaxf(m0, m1), fmaxf(m2, m3));
                    const float e0 = exp2f((m0 - mm) * SC), e1 = exp2f((m1 - mm) * SC), e2 = exp2f((m2 - mm) * SC), e3 = exp2f((m3 - mm) * SC);
                    const float inv = 1.f / ((e0 * u2f(sv0.y) + e1 * u2f(sv0.w)) + (e2 * u2f(sv1.y) + e3 * u2f(sv1.w)));
                    w0 = e0 * inv; w1 = e1 * inv; w2 = e2 * inv; w3 = e3 * inv;
                } else {
                    sv0 = ld_mail4(st_src); sv1 = ld_mail4(st_src + 4);
                }
            }
#pragma unroll
            for (int i = 0; i < 4; i++) if (!ok[i]) ok[i] = __all_sync(0xffffffffu, tag_ok(v[i], tag));
            if (sok && ok[0] && ok[1] && ok[2] && ok[3]) break;
            if (++it > SPIN_LIMIT) __trap();
        }
        TS(20);
        const float r0 = w0 * u2f(v[0].x) + w1 * u2f(v[1].x) + w2 * u2f(v[2].x) + w3 * u2f(v[3].x);
        const float r1 = w0 * u2f(v[0].y) + w1 * u2f(v[1].y) + w2 * u2f(v[2].y) + w3 * u2f(v[3].y);
        const float r2 = w0 * u2f(v[0].z) + w1 * u2f(v[1].z) + w2 * u2f(v[2].z) + w3 * u2f(v[3].z);
        const float r3 = w0 * u2f(v[0].w) + w1 * u2f(v[1].w) + w2 * u2f(v[2].w) + w3 * u2f(v[3].w);
        *reinterpret_cast<uint2*>(smem + OFF_OS + warp * 272 + lane * 8) = make_uint2(pack_bf16(r0, r1), pack_bf16(r2, r3));
        TS(8);
        asm volatile("bar.arrive 4, 256;" ::: "memory");

        uint4 pv[1];
        asm volatile("bar.sync 5, 256;" ::: "memory");
        poll_mail<1>(pv, g_p + cta * 512 + warp * 128 + 4 * lane, 0, tag);
        TS(10);
        float s0 = u2f(pv[0].x), s1 = u2f(pv[0].y), s2 = u2f(pv[0].z), s3 = u2f(pv[0].w);
#pragma unroll
        for (int o = 4; o < 32; o <<= 1) {
            s0 += __shfl_xor_sync(0xffffffffu, s0, o);
            s1 += __shfl_xor_sync(0xffffffffu, s1, o);
            s2 += __shfl_xor_sync(0xffffffffu, s2, o);
            s3 += __shfl_xor_sync(0xffffffffu, s3, o);
        }
        float* redq = reinterpret_cast<float*>(smem + OFF_REDQ);
        if (lane < 4) *reinterpret_cast<float4*>(redq + warp * 16 + lane * 4) = make_float4(s0, s1, s2, s3);
        asm volatile("bar.sync 3, 128;" ::: "memory");
        if (warp == 0 && lane < 16) {
            const int b = lane >> 2, c = lane & 3;
            const float r = (redq[c * 4 + b] + redq[16 + c * 4 + b]) + (redq[32 + c * 4 + b] + redq[48 + c * 4 + b]);
            prm.out[b * D_MODEL + 4 * cta + c] = __float2bfloat16(r);
            if (lane == 0) g_epoch[cta * 32] = epoch + 1;
        }
        TS(11);
    } else {
        const int q = warp - 4;
        const uint32_t aoff = (q >> 1) * 4096 + (i8 + 8 * (j8 >> 1)) * 128;
        uint32_t aw[4][2][2][4];
#pragma unroll
        for (int c = 0; c < 4; c++) {
            mbar_wait_warp(bar0 + 8 * (C_WO + c));
#pragma unroll
            for (int ks = 0; ks < 2; ks++)
#pragma unroll
                for (int mt = 0; mt < 2; mt++)
                    ldsm4t(aw[c][ks][mt], sb + OFF_A + c * 8192 + aoff + ks * 2048 + (((4 * (q & 1) + 2 * mt + (j8 & 1)) ^ i8) << 4));
        }
        const float2 gt = *reinterpret_cast<const float2*>(smem + OFF_GATE + 4 * bp);
        TS(13);
        asm volatile("bar.sync 4, 256;" ::: "memory");
        uint32_t of[4][4], af[2][4];
#pragma unroll
        for (int u = 0; u < 4; u++) ldsm4(of[u], sb + OFF_OS + (i8 & 3) * 272 + (32 * u + 8 * j8) * 2);
#pragma unroll
        for (int u = 0; u < 2; u++) ldsm4(af[u], sb + OFF_AS + (i8 & 3) * 144 + (32 * u + 8 * j8) * 2);
        float acc[2][2][4] = {}, bb[2][4] = {};
#pragma unroll
        for (int c = 0; c < 4; c++)
#pragma unroll
            for (int ks = 0; ks < 2; ks++)
#pragma unroll
                for (int mt = 0; mt < 2; mt++) mma16816(acc[mt][ks], aw[c][ks][mt], of[c][2 * ks], of[c][2 * ks + 1]);
        TS(14);
        if (ffn) {
#pragma unroll
            for (int c = 0; c < 2; c++) {
                mbar_wait_warp(bar0 + 8 * (C_W2 + c));
#pragma unroll
                for (int ks = 0; ks < 2; ks++)
#pragma unroll
                    for (int mt = 0; mt < 2; mt++) {
                        uint32_t a[4];
                        ldsm4t(a, sb + OFF_W2 + c * 8192 + aoff + ks * 2048 + (((4 * (q & 1) + 2 * mt + (j8 & 1)) ^ i8) << 4));
                        mma16816(bb[mt], a, af[c][2 * ks], af[c][2 * ks + 1]);
                    }
            }
        }
        TS(9);
#pragma unroll
        for (int mt = 0; mt < 2; mt++) {
            const float va = hi ? acc[mt][0][2] + acc[mt][1][2] : acc[mt][0][0] + acc[mt][1][0];
            const float vb = hi ? acc[mt][0][3] + acc[mt][1][3] : acc[mt][0][1] + acc[mt][1][1];
            const float ba = hi ? bb[mt][2] : bb[mt][0], bv = hi ? bb[mt][3] : bb[mt][1];
            st_mail2(p_slot + mt * (4 * 32 * 16), tagw(gt.x * va + (1.f - gt.x) * ba, tag), tagw(gt.y * vb + (1.f - gt.y) * bv, tag));
        }
        asm volatile("bar.arrive 5, 256;" ::: "memory");
        TS(16);
    }
    TS_DUMP();
}

typedef CUresult (*EncodeTiledFn)(CUtensorMap*, CUtensorMapDataType, cuuint32_t, void*, const cuuint64_t*,
                                  const cuuint64_t*, const cuuint32_t*, const cuuint32_t*, CUtensorMapInterleave,
                                  CUtensorMapSwizzle, CUtensorMapL2promotion, CUtensorMapFloatOOBfill);

#define L2PROMO CU_TENSOR_MAP_L2_PROMOTION_L2_128B

#define WQPROMO L2PROMO
void encode2d(EncodeTiledFn fn, CUtensorMap* m, const void* base, uint64_t cols, uint64_t rows,
              uint32_t boxc, uint32_t boxr, CUtensorMapSwizzle sw, CUtensorMapL2promotion promo = L2PROMO) {
    cuuint64_t dims[2] = {cols, rows};
    cuuint64_t str[1] = {cols * 2};
    cuuint32_t box[2] = {boxc, boxr}, es[2] = {1, 1};
    fn(m, CU_TENSOR_MAP_DATA_TYPE_BFLOAT16, 2, const_cast<void*>(base), dims, str, box, es,
       CU_TENSOR_MAP_INTERLEAVE_NONE, sw, promo, CU_TENSOR_MAP_FLOAT_OOB_FILL_NONE);
}
void encode3d(EncodeTiledFn fn, CUtensorMap* m, const void* base, uint64_t cols, uint64_t rows, uint32_t boxr) {
    cuuint64_t dims[3] = {64, rows, cols / 64};
    cuuint64_t str[2] = {cols * 2, 128};
    cuuint32_t box[3] = {64, boxr, 2}, es[3] = {1, 1, 1};
    fn(m, CU_TENSOR_MAP_DATA_TYPE_BFLOAT16, 3, const_cast<void*>(base), dims, str, box, es,
       CU_TENSOR_MAP_INTERLEAVE_NONE, CU_TENSOR_MAP_SWIZZLE_128B, L2PROMO, CU_TENSOR_MAP_FLOAT_OOB_FILL_NONE);
}

}

extern "C" void kernel_launch(void* const* d_in, const int* in_sizes, int n_in, void* d_out, int out_size) {
    (void)in_sizes; (void)n_in; (void)out_size;
    static EncodeTiledFn fn = nullptr;
    static float* scratch = nullptr;
    if (!fn) {
        void* p = nullptr;
        cudaDriverEntryPointQueryResult st;
        cudaGetDriverEntryPoint("cuTensorMapEncodeTiled", &p, cudaEnableDefault, &st);
        fn = reinterpret_cast<EncodeTiledFn>(p);
        cudaFuncSetAttribute(gated_mix_kernel, cudaFuncAttributeMaxDynamicSharedMemorySize, SMEM_BYTES);
        void* sp = nullptr;
        cudaGetSymbolAddress(&sp, g_scratch);
        scratch = static_cast<float*>(sp);
    }
    Params prm;
    prm.x = static_cast<const __nv_bfloat16*>(d_in[0]);
    prm.b1 = static_cast<const __nv_bfloat16*>(d_in[7]);
    prm.gate_w = static_cast<const __nv_bfloat16*>(d_in[9]);
    prm.out = static_cast<__nv_bfloat16*>(d_out);
    prm.wq = static_cast<const char*>(d_in[3]);
    prm.scratch = scratch;
    encode2d(fn, &prm.m_wq, d_in[3], HQ * DH, D_MODEL, 32, 128, CU_TENSOR_MAP_SWIZZLE_64B, WQPROMO);
    encode2d(fn, &prm.m_w1, d_in[6], FF, D_MODEL, 64, 64, CU_TENSOR_MAP_SWIZZLE_128B);
    encode3d(fn, &prm.m_k, d_in[1], DH, (uint64_t)4 * HKV * SK, 32);
    encode3d(fn, &prm.m_v, d_in[2], DH, (uint64_t)4 * HKV * SK, 32);
    encode3d(fn, &prm.m_wo, d_in[4], D_MODEL, HQ * DH, 32);
    encode3d(fn, &prm.m_w2, d_in[8], D_MODEL, FF, 32);
    gated_mix_kernel<<<NCTA, NTHREADS, SMEM_BYTES, cudaStreamPerThread>>>(prm);
}
```

```cpp
#include <cuda_runtime.h>
#include <cuda_bf16.h>
#include <cuda.h>
#include <stdint.h>

namespace {

constexpr int NCTA = 128;
constexpr int NTHREADS = 288;
#define PACE_NS 355
#define PACE_LEAD 4
#define PACE_T0 500
#define WINDOW 7
#define Q_AFTER_K 1
#define A_POS 2
#define O_AFTER 1

constexpr int D_MODEL = 512, HQ = 32, HKV = 8, SK = 4096, WIN = 1024, DH = 128, FF = 1792;

constexpr int C_WQ = 0, C_W1 = 4, C_K = 6, C_V = 14, C_WO = 22, C_W2 = 26, NCHUNK = 28;
constexpr int C_TAIL = C_V + 8;
constexpr int NSLOT = 11;
constexpr int OFF_XS = NSLOT * 8192;
constexpr int OFF_RED = OFF_XS + 4 * 1040;
constexpr int OFF_PALL = OFF_RED + 4096;
constexpr int OFF_QS = OFF_PALL + 4 * 2112;
constexpr int OFF_AS = OFF_QS + 4 * 272;
constexpr int OFF_HBUF = OFF_AS + 4 * 464;
constexpr int OFF_SBUF = OFF_HBUF + 1792;
constexpr int OFF_PBUF = OFF_SBUF + 128;
constexpr int OFF_WMAX = OFF_PBUF + 2048;
constexpr int OFF_WSUM = OFF_WMAX + 128;
constexpr int OFF_GATE = OFF_WSUM + 128;
constexpr int OFF_EPOCH = OFF_GATE + 16;
constexpr int OFF_BAR = OFF_EPOCH + 16;
constexpr int B_EMPTY = NSLOT, B_H = 2 * NSLOT, B_P = B_H + 1, B_OUT = B_H + 2, NBAR = B_H + 3;
constexpr int SMEM_BYTES = OFF_BAR + NBAR * 8;
static_assert(OFF_BAR % 8 == 0 && OFF_PALL % 16 == 0 && OFF_PBUF % 16 == 0 && OFF_QS % 16 == 0 && OFF_AS % 16 == 0, "align");
static_assert(SMEM_BYTES <= 115712, "two CTAs must fit on one SM so that all 16 clusters are co-resident");

struct alignas(64) Params {
    const __nv_bfloat16* x;
    const __nv_bfloat16* b1;
    const __nv_bfloat16* gate_w;
    __nv_bfloat16* out;
    const char* wq;
    float* scratch;
    alignas(64) CUtensorMap m_wq;
    alignas(64) CUtensorMap m_w1;
    alignas(64) CUtensorMap m_k;
    alignas(64) CUtensorMap m_v;
    alignas(64) CUtensorMap m_wo;
    alignas(64) CUtensorMap m_w2;
};

constexpr int SC_EPOCH = 0;
constexpr int SC_Q = SC_EPOCH + NCTA * 32;
constexpr int SC_A = SC_Q + 4 * HQ * DH;
constexpr int SC_O = SC_A + FF * 4;
constexpr int SC_TOTAL = SC_O + 4 * HQ * DH;
__device__ __align__(128) float g_scratch[SC_TOTAL];
#define TS(k)
#define TS_DUMP()

__device__ __forceinline__ uint32_t smem_u32(const void* p) { return (uint32_t)__cvta_generic_to_shared(p); }
__device__ __forceinline__ void mbar_init(uint32_t bar, uint32_t cnt) {
    asm volatile("mbarrier.init.shared::cta.b64 [%0], %1;" :: "r"(bar), "r"(cnt) : "memory");
}
__device__ __forceinline__ void mbar_expect_tx(uint32_t bar, uint32_t bytes) {
    asm volatile("mbarrier.arrive.expect_tx.shared::cta.b64 _, [%0], %1;" :: "r"(bar), "r"(bytes) : "memory");
}
__device__ __forceinline__ void mbar_arrive_n(uint32_t bar, uint32_t n) {
    asm volatile("mbarrier.arrive.shared::cta.b64 _, [%0], %1;" :: "r"(bar), "r"(n) : "memory");
}
__device__ __forceinline__ bool mbar_try(uint32_t bar, uint32_t parity) {
    uint32_t ok;
    asm volatile("{\n.reg .pred p;\nmbarrier.try_wait.parity.shared::cta.b64 p, [%1], %2;\nselp.u32 %0, 1, 0, p;\n}"
                 : "=r"(ok) : "r"(bar), "r"(parity) : "memory");
    return ok;
}
__device__ __forceinline__ bool mbar_try_cluster(uint32_t bar) {
    uint32_t ok;
    asm volatile("{\n.reg .pred p;\nmbarrier.try_wait.parity.acquire.cluster.shared::cta.b64 p, [%1], 0;\nselp.u32 %0, 1, 0, p;\n}"
                 : "=r"(ok) : "r"(bar) : "memory");
    return ok;
}
constexpr int SPIN_LIMIT = 1 << 22;
__device__ __forceinline__ void mbar_wait(uint32_t bar, uint32_t parity) {
    int it = 0;
    while (!mbar_try(bar, parity)) { if (++it > SPIN_LIMIT) __trap(); }
}
__device__ __forceinline__ void mbar_wait_cluster(uint32_t bar) {
    int it = 0;
    while (!mbar_try_cluster(bar)) { if (++it > SPIN_LIMIT) __trap(); }
    __syncwarp();
}
__device__ __forceinline__ void tma2d(uint32_t dst, const CUtensorMap* m, int c0, int c1, uint32_t bar, uint64_t pol) {
    asm volatile("cp.async.bulk.tensor.2d.shared::cluster.global.mbarrier::complete_tx::bytes.L2::cache_hint"
                 " [%0], [%1, {%3, %4}], [%2], %5;"
                 :: "r"(dst), "l"(m), "r"(bar), "r"(c0), "r"(c1), "l"(pol) : "memory");
}
__device__ __forceinline__ void tma3d(uint32_t dst, const CUtensorMap* m, int c0, int c1, int c2, uint32_t bar, uint64_t pol) {
    asm volatile("cp.async.bulk.tensor.3d.shared::cluster.global.mbarrier::complete_tx::bytes.L2::cache_hint"
                 " [%0], [%1, {%3, %4, %5}], [%2], %6;"
                 :: "r"(dst), "l"(m), "r"(bar), "r"(c0), "r"(c1), "r"(c2), "l"(pol) : "memory");
}
__device__ __forceinline__ void tma4d(uint32_t dst, const CUtensorMap* m, int c0, int c1, int c2, int c3, uint32_t bar, uint64_t pol) {
    asm volatile("cp.async.bulk.tensor.4d.shared::cluster.global.mbarrier::complete_tx::bytes.L2::cache_hint"
                 " [%0], [%1, {%3, %4, %5, %6}], [%2], %7;"
                 :: "r"(dst), "l"(m), "r"(bar), "r"(c0), "r"(c1), "r"(c2), "r"(c3), "l"(pol) : "memory");
}
__device__ __forceinline__ uint32_t mapa(uint32_t a, uint32_t rank) {
    uint32_t d;
    asm("mapa.shared::cluster.u32 %0, %1, %2;" : "=r"(d) : "r"(a), "r"(rank));
    return d;
}
__device__ __forceinline__ void st_async2(uint32_t addr, float a, float b, uint32_t bar) {
    asm volatile("st.async.weak.shared::cluster.mbarrier::complete_tx::bytes.v2.f32 [%0], {%1, %2}, [%3];"
                 :: "r"(addr), "f"(a), "f"(b), "r"(bar) : "memory");
}
__device__ __forceinline__ void bulk_s2dsm(uint32_t dst, uint32_t src, uint32_t bytes, uint32_t bar) {
    asm volatile("cp.async.bulk.shared::cluster.shared::cta.mbarrier::complete_tx::bytes [%0], [%1], %2, [%3];"
                 :: "r"(dst), "r"(src), "r"(bytes), "r"(bar) : "memory");
}
__device__ __forceinline__ void ldsm4(uint32_t (&r)[4], uint32_t a) {
    asm volatile("ldmatrix.sync.aligned.m8n8.x4.shared.b16 {%0,%1,%2,%3}, [%4];"
                 : "=r"(r[0]), "=r"(r[1]), "=r"(r[2]), "=r"(r[3]) : "r"(a) : "memory");
}
__device__ __forceinline__ void ldsm4t(uint32_t (&r)[4], uint32_t a) {
    asm volatile("ldmatrix.sync.aligned.m8n8.x4.trans.shared.b16 {%0,%1,%2,%3}, [%4];"
                 : "=r"(r[0]), "=r"(r[1]), "=r"(r[2]), "=r"(r[3]) : "r"(a) : "memory");
}
__device__ __forceinline__ void stsm4t(uint32_t a, uint32_t r0, uint32_t r1, uint32_t r2, uint32_t r3) {
    asm volatile("stmatrix.sync.aligned.m8n8.x4.trans.shared.b16 [%0], {%1,%2,%3,%4};"
                 :: "r"(a), "r"(r0), "r"(r1), "r"(r2), "r"(r3) : "memory");
}
__device__ __forceinline__ void mma16816(float (&c)[4], const uint32_t (&a)[4], uint32_t b0, uint32_t b1) {
    asm volatile("mma.sync.aligned.m16n8k16.row.col.f32.bf16.bf16.f32 {%0,%1,%2,%3}, {%4,%5,%6,%7}, {%8,%9}, {%0,%1,%2,%3};"
                 : "+f"(c[0]), "+f"(c[1]), "+f"(c[2]), "+f"(c[3])
                 : "r"(a[0]), "r"(a[1]), "r"(a[2]), "r"(a[3]), "r"(b0), "r"(b1));
}
__device__ __forceinline__ uint32_t pack_bf16(float lo, float hi) {
    uint32_t r;
    asm("cvt.rn.bf16x2.f32 %0, %1, %2;" : "=r"(r) : "f"(hi), "f"(lo));
    return r;
}
__device__ __forceinline__ void csync() { asm volatile("bar.sync 1, 256;" ::: "memory"); }

__device__ __forceinline__ uint32_t tagw(float v, uint32_t tag) { return (__float_as_uint(v) & ~3u) | tag; }
__device__ __forceinline__ void st_mail(float* p, uint32_t v) {
    asm volatile("st.relaxed.gpu.global.b32 [%0], %1;" :: "l"(p), "r"(v) : "memory");
}
__device__ __forceinline__ uint4 ld_mail4(const float* p) {
    uint4 v;
    asm volatile("ld.relaxed.gpu.global.v4.b32 {%0,%1,%2,%3}, [%4];" : "=r"(v.x), "=r"(v.y), "=r"(v.z), "=r"(v.w) : "l"(p) : "memory");
    return v;
}
__device__ __forceinline__ bool tag_ok(const uint4& v, uint32_t tag) {
    return (((v.x ^ tag) | (v.y ^ tag) | (v.z ^ tag) | (v.w ^ tag)) & 3u) == 0;
}
template <int N>
__device__ __forceinline__ void poll_mail(uint4 (&v)[N], const float* p, int stride, uint32_t tag) {
    bool ok[N];
#pragma unroll
    for (int i = 0; i < N; i++) ok[i] = false;
    int it = 0;
    while (true) {
#pragma unroll
        for (int i = 0; i < N; i++) if (!ok[i]) v[i] = ld_mail4(p + i * stride);
        bool all = true;
#pragma unroll
        for (int i = 0; i < N; i++) { if (!ok[i]) ok[i] = __all_sync(0xffffffffu, tag_ok(v[i], tag)); all = all && ok[i]; }
        if (all) break;
        if (++it > SPIN_LIMIT) __trap();
    }
}
__device__ __forceinline__ float u2f(uint32_t u) { return __uint_as_float(u); }
__device__ __forceinline__ uint64_t gtime() { uint64_t t; asm volatile("mov.u64 %0, %globaltimer;" : "=l"(t)); return t; }
__device__ __forceinline__ float mish(float h) {
    const float e = __expf(fminf(h, 30.f));
    const float n = e * (e + 2.f);
    return h * __fdividef(n, n + 2.f);
}
__device__ __forceinline__ uint32_t addr64(int row, int chunk16) { return row * 64 + ((chunk16 ^ ((row >> 1) & 3)) << 4); }

__global__ void __cluster_dims__(8, 1, 1) __launch_bounds__(NTHREADS, 2)
gated_mix_kernel(const __grid_constant__ Params prm) {
    extern __shared__ __align__(1024) unsigned char smem[];
    const uint32_t sb = smem_u32(smem);
    const int warp = threadIdx.x >> 5, lane = threadIdx.x & 31;
    const int cta = blockIdx.x;
    const int cl = cta >> 3, rk = cta & 7;
    const uint32_t bar0 = sb + OFF_BAR;
    auto full_bar = [&](int j) { return bar0 + 8 * (j % NSLOT); };
    auto empty_bar = [&](int j) { return bar0 + 8 * (B_EMPTY + j % NSLOT); };
    auto slot = [&](int j) { return sb + (j % NSLOT) * 8192; };
    auto wait_full = [&](int j) { mbar_wait(full_bar(j), (j / NSLOT) & 1); __syncwarp(); };
    if (threadIdx.x == 0)
        asm volatile("cp.async.bulk.prefetch.L2.global [%0], %1;" :: "l"(prm.wq + (size_t)cta * 32768), "r"(32768) : "memory");

    if (warp == 8) {
        const uint64_t t0 = gtime() + PACE_T0;
        TS(0);
        uint64_t pol;
        asm volatile("createpolicy.fractional.L2::evict_first.b64 %0, 1.0;" : "=l"(pol));
        const int pair = cta >> 2, sp = cta & 3;
        const int krow = pair * SK + (SK - WIN) + sp * 256;
        auto issue = [&](int j) {
            const uint32_t bar = full_bar(j), dst = slot(j);
            mbar_expect_tx(bar, 8192);
            if (j < 4)                               tma2d(dst, &prm.m_wq, cta * 32, j * 128, bar, pol);
            else if (j >= C_W1 && j < C_W1 + 2)      tma2d(dst, &prm.m_w1, cl * 112 + (j - C_W1) * 64, rk * 64, bar, pol);
            else if (j >= C_K && j < C_K + 8)        tma3d(dst, &prm.m_k, 0, krow + (j - C_K) * 32, 0, bar, pol);
            else if (j >= C_V && j < C_V + 8)        tma4d(dst, &prm.m_v, sp * 32, (j - C_V) * 32, 0, pair, bar, pol);
            else if (j >= C_WO && j < C_WO + 4)      tma2d(dst, &prm.m_wo, cl * 32, rk * 512 + (j - C_WO) * 128, bar, pol);
            else                                     tma2d(dst, &prm.m_w2, cl * 32, rk * 224 + (j - C_W2) * 128, bar, pol);
        };
        if (lane == 0) {
#pragma unroll
            for (int j = 0; j < 4; j++) { mbar_init(full_bar(j), 1); issue(j); }
            asm volatile("prefetch.tensormap [%0];" :: "l"(&prm.m_w1) : "memory");
            asm volatile("prefetch.tensormap [%0];" :: "l"(&prm.m_k) : "memory");
            TS(1);
        }
        __syncwarp();
        asm volatile("bar.sync 2, 288;" ::: "memory");
        asm volatile("barrier.cluster.arrive.relaxed.aligned;" ::: "memory");
        if (lane == 0) {
            asm volatile("prefetch.tensormap [%0];" :: "l"(&prm.m_v) : "memory");
            asm volatile("prefetch.tensormap [%0];" :: "l"(&prm.m_wo) : "memory");
            asm volatile("prefetch.tensormap [%0];" :: "l"(&prm.m_w2) : "memory");
#pragma unroll
            for (int j = 4; j < NCHUNK; j++) {
                if (j >= WINDOW) { mbar_wait(full_bar(j - WINDOW), ((j - WINDOW) / NSLOT) & 1); TS(32 + j - WINDOW); }
                if (j >= NSLOT) mbar_wait(empty_bar(j), ((j - NSLOT) / NSLOT) & 1);
                { int it = 0; while ((long long)(gtime() - t0) < (long long)((j - PACE_LEAD) * PACE_NS) && ++it < SPIN_LIMIT) {} }
                issue(j);
            }
        }
        TS_DUMP();
        return;
    }

    const int g = lane >> 2, t = lane & 3;
    const int j8 = lane >> 3, i8 = lane & 7;
    const int hi = t >> 1, bp = 2 * (t & 1);
    const int tid = threadIdx.x;
    float* const g_q = prm.scratch + SC_Q;
    float* const g_a = prm.scratch + SC_A;
    float* const g_o = prm.scratch + SC_O;
    unsigned int* const g_epoch = reinterpret_cast<unsigned int*>(prm.scratch) + SC_EPOCH;
    const int ab = cta >> 5, ahkv = (cta >> 2) & 7, as = cta & 3;

    uint4 xv0, xv1;
    unsigned int epoch = 0;
    float* const q_slot = g_q + ((tid & 3) * HQ + (cta >> 2)) * DH + 32 * (cta & 3) + ((tid >> 2) & 31);
    if (warp < 4) {
        xv0 = __ldg(reinterpret_cast<const uint4*>(prm.x) + tid);
        xv1 = __ldg(reinterpret_cast<const uint4*>(prm.x) + 128 + tid);
        if (tid == 0) asm volatile("ld.relaxed.gpu.global.u32 %0, [%1];" : "=r"(epoch) : "l"(&g_epoch[cta * 32]) : "memory");
        st_mail(q_slot, 0u);
    } else {
        if (lane == 0) {
            if (warp == 4) {
#pragma unroll
                for (int b = 4; b < 10; b++) mbar_init(bar0 + 8 * b, 1);
            } else if (warp == 5) {
                mbar_init(bar0 + 8 * 10, 1);
#pragma unroll
                for (int b = 0; b < 4; b++) mbar_init(bar0 + 8 * (B_EMPTY + b), 8);
            } else if (warp == 6) {
#pragma unroll
                for (int b = 4; b < 9; b++) mbar_init(bar0 + 8 * (B_EMPTY + b), 8);
            } else {
                mbar_init(bar0 + 8 * (B_EMPTY + 9), 8);
                mbar_init(bar0 + 8 * (B_EMPTY + 10), 8);
                mbar_init(bar0 + 8 * B_H, 1);   mbar_expect_tx(bar0 + 8 * B_H, 1792);
                mbar_init(bar0 + 8 * B_P, 1);   mbar_expect_tx(bar0 + 8 * B_P, 3 * (2112 + 32));
                mbar_init(bar0 + 8 * B_OUT, 1); mbar_expect_tx(bar0 + 8 * B_OUT, 2048);
            }
            asm volatile("fence.mbarrier_init.release.cluster;" ::: "memory");
        }
        __syncwarp();
    }
    TS(22);
    asm volatile("bar.sync 2, 288;" ::: "memory");
    asm volatile("barrier.cluster.arrive.relaxed.aligned;" ::: "memory");
    TS(23);

    if (warp < 4) {
        *reinterpret_cast<uint4*>(smem + OFF_XS + (tid >> 6) * 1040 + (tid & 63) * 16) = xv0;
        *reinterpret_cast<uint4*>(smem + OFF_XS + (2 + (tid >> 6)) * 1040 + (tid & 63) * 16) = xv1;
    }
    TS(24);
    csync();
    uint32_t xq[2][4];
#pragma unroll
    for (int u = 0; u < 2; u++) ldsm4(xq[u], sb + OFF_XS + (i8 & 3) * 1040 + (64 * warp + 32 * u + 8 * j8) * 2);
    TS(0);
    uint32_t tag;

    {
        float aq[2][4] = {};
        const int j = C_WQ + (warp >> 1);
        wait_full(j);
        TS(2);
#pragma unroll
        for (int ks = 0; ks < 4; ks++) {
            const int row = 64 * (warp & 1) + 16 * ks + i8 + 8 * (j8 >> 1);
#pragma unroll
            for (int mt = 0; mt < 2; mt++) {
                uint32_t a[4];
                ldsm4t(a, slot(j) + addr64(row, 2 * mt + (j8 & 1)));
                mma16816(aq[mt], a, xq[ks >> 1][2 * (ks & 1)], xq[ks >> 1][2 * (ks & 1) + 1]);
            }
        }
        __syncwarp();
        if (lane == 0) mbar_arrive_n(empty_bar(j), 4);
        float* redq = reinterpret_cast<float*>(smem + OFF_RED);
        {
            const float v0 = hi ? aq[1][0] : aq[0][0], v1 = hi ? aq[1][1] : aq[0][1];
            const float v2 = hi ? aq[1][2] : aq[0][2], v3 = hi ? aq[1][3] : aq[0][3];
            *reinterpret_cast<float2*>(redq + (warp * 32 + 16 * hi + g) * 4 + bp) = make_float2(v0, v1);
            *reinterpret_cast<float2*>(redq + (warp * 32 + 16 * hi + g + 8) * 4 + bp) = make_float2(v2, v3);
        }
        if (tid == 0) *reinterpret_cast<unsigned int*>(smem + OFF_EPOCH) = epoch;
        csync();
        epoch = *reinterpret_cast<const unsigned int*>(smem + OFF_EPOCH);
        tag = 1u + (epoch & 1u);
        if (tid < 128) {
            float s = 0.f;
#pragma unroll
            for (int w = 0; w < 8; w++) s += redq[w * 128 + tid];
            st_mail(q_slot, (pack_bf16(0.f, s) & 0xffff0000u) | tag);
        }
        TS(3);
    }

    float* const o_slot = g_o + (ab * HQ + 4 * ahkv + (tid >> 5)) * DH + 32 * as + (tid & 31);
    float* const a_slot = g_a + (112 * cl + 14 * rk) * 4 + (tid - 128);
    if (tid < 128) st_mail(o_slot, 0u);
    else if (tid < 128 + 56) st_mail(a_slot, 0u);
    asm volatile("barrier.cluster.wait.aligned;" ::: "memory");

    uint32_t xh[2][4];
    if (warp >= 4) {
#pragma unroll
        for (int u = 0; u < 2; u++) ldsm4(xh[u], sb + OFF_XS + (i8 & 3) * 1040 + (64 * rk + 32 * u + 8 * j8) * 2);
    }
    auto h_partial = [&](const uint32_t (&xf)[2][4]) {
        const int b = warp - 4;
        const int j = C_W1 + (b >> 1);
        wait_full(j);
        float h[2][4] = {};
#pragma unroll
        for (int ks = 0; ks < 4; ks++) {
            const int row = 16 * ks + i8 + 8 * (j8 >> 1);
#pragma unroll
            for (int m = 0; m < 2; m++) {
                uint32_t a[4];
                ldsm4t(a, slot(j) + row * 128 + (((4 * (b & 1) + 2 * m + (j8 & 1)) ^ (row & 7)) << 4));
                mma16816(h[m], a, xf[ks >> 1][2 * (ks & 1)], xf[ks >> 1][2 * (ks & 1) + 1]);
            }
        }
        if (C_W1 + NSLOT < NCHUNK) { __syncwarp(); if (lane == 0) mbar_arrive_n(empty_bar(j), 4); }
#pragma unroll
        for (int m = 0; m < 2; m++) {
            const int u = 16 * (2 * b + m) + g + 8 * hi;
            if (u < 112) {
                const int owner = u / 14, ul = u - 14 * owner;
                st_async2(mapa(sb + OFF_HBUF + ((rk * 14 + ul) * 4 + bp) * 4, owner),
                          hi ? h[m][2] : h[m][0], hi ? h[m][3] : h[m][1], mapa(bar0 + 8 * B_H, owner));
            }
        }
    };
    const float* gate_s = reinterpret_cast<const float*>(smem + OFF_GATE);
    auto activation = [&]() {
        const int tt = tid - 128;
        const float bias = tt < 56 ? __bfloat162float(prm.b1[112 * cl + 14 * rk + (tt >> 2)]) : 0.f;
        mbar_wait_cluster(bar0 + 8 * B_H);
        if (tt < 56) {
            const float* hb = reinterpret_cast<const float*>(smem + OFF_HBUF);
            float h = bias;
#pragma unroll
            for (int src = 0; src < 8; src++) h += hb[src * 56 + tt];
            st_mail(a_slot, tagw(mish(h) * (1.f - gate_s[tt & 3]), tag));
        }
        __syncwarp();
    };

    if (warp < 4) {
        wait_full(C_K + Q_AFTER_K);
        uint4 v[1];
        poll_mail<1>(v, g_q + (ab * HQ + 4 * ahkv + warp) * DH + 4 * lane, 0, tag);
        const uint32_t p0 = (v[0].x >> 16) | (v[0].y & 0xffff0000u), p1 = (v[0].z >> 16) | (v[0].w & 0xffff0000u);
        *reinterpret_cast<uint2*>(smem + OFF_QS + warp * 272 + lane * 8) = make_uint2(p0, p1);
        TS(21);
    } else {
        const int b = warp - 4;
        const uint4* gr = reinterpret_cast<const uint4*>(prm.gate_w);
        const uint4 gv0 = __ldg(gr + lane), gv1 = __ldg(gr + 32 + lane);
        h_partial(xh);
        float s = 0.f;
#pragma unroll
        for (int u = 0; u < 2; u++) {
            const uint4 xx = *reinterpret_cast<const uint4*>(smem + OFF_XS + b * 1040 + (u * 32 + lane) * 16), gv = u ? gv1 : gv0;
            const uint32_t xa[4] = {xx.x, xx.y, xx.z, xx.w}, ga[4] = {gv.x, gv.y, gv.z, gv.w};
#pragma unroll
            for (int e = 0; e < 4; e++) {
                s = fmaf(u2f(xa[e] << 16), u2f(ga[e] << 16), s);
                s = fmaf(u2f(xa[e] & 0xffff0000u), u2f(ga[e] & 0xffff0000u), s);
            }
        }
#pragma unroll
        for (int o = 16; o > 0; o >>= 1) s += __shfl_xor_sync(0xffffffffu, s, o);
        if (lane == 0) reinterpret_cast<float*>(smem + OFF_GATE)[b] = 1.f / (1.f + __expf(-s));
    }
    csync();

    constexpr float SC = 0.08838834764831845f * 1.4426950408889634f;
    float* wmax = reinterpret_cast<float*>(smem + OFF_WMAX);
    float* wsum = reinterpret_cast<float*>(smem + OFF_WSUM);
    {
        uint32_t qf[4][4];
#pragma unroll
        for (int u = 0; u < 4; u++) ldsm4(qf[u], sb + OFF_QS + (i8 & 3) * 272 + (32 * u + 8 * j8) * 2);
        TS(4);
        float s[2][4] = {};
        const int j = C_K + warp;
        wait_full(j);
        TS(5);
#pragma unroll
        for (int ks = 0; ks < 8; ks++) {
#pragma unroll
            for (int mt = 0; mt < 2; mt++) {
                const int row = 16 * mt + i8 + 8 * (j8 & 1);
                uint32_t a[4];
                ldsm4(a, slot(j) + (ks >> 2) * 4096 + row * 128 + (((2 * (ks & 3) + (j8 >> 1)) ^ (row & 7)) << 4));
                mma16816(s[mt], a, qf[ks >> 1][2 * (ks & 1)], qf[ks >> 1][2 * (ks & 1) + 1]);
            }
        }
        __syncwarp();
        if (lane == 0) mbar_arrive_n(empty_bar(j), 8);
        float m0 = fmaxf(fmaxf(s[0][0], s[0][2]), fmaxf(s[1][0], s[1][2]));
        float m1 = fmaxf(fmaxf(s[0][1], s[0][3]), fmaxf(s[1][1], s[1][3]));
#pragma unroll
        for (int o = 4; o < 32; o <<= 1) {
            m0 = fmaxf(m0, __shfl_xor_sync(0xffffffffu, m0, o));
            m1 = fmaxf(m1, __shfl_xor_sync(0xffffffffu, m1, o));
        }
        if (lane < 2) *reinterpret_cast<float2*>(wmax + warp * 4 + 2 * lane) = make_float2(m0, m1);
        csync();
        m0 = -INFINITY; m1 = -INFINITY;
#pragma unroll
        for (int w = 0; w < 8; w++) {
            const float2 mm = *reinterpret_cast<const float2*>(wmax + w * 4 + bp);
            m0 = fmaxf(m0, mm.x); m1 = fmaxf(m1, mm.y);
        }
        float p[2][4];
#pragma unroll
        for (int mt = 0; mt < 2; mt++) {
            p[mt][0] = exp2f((s[mt][0] - m0) * SC); p[mt][1] = exp2f((s[mt][1] - m1) * SC);
            p[mt][2] = exp2f((s[mt][2] - m0) * SC); p[mt][3] = exp2f((s[mt][3] - m1) * SC);
        }
        float l0 = (p[0][0] + p[0][2]) + (p[1][0] + p[1][2]), l1 = (p[0][1] + p[0][3]) + (p[1][1] + p[1][3]);
#pragma unroll
        for (int o = 4; o < 32; o <<= 1) {
            l0 += __shfl_xor_sync(0xffffffffu, l0, o);
            l1 += __shfl_xor_sync(0xffffffffu, l1, o);
        }
        if (lane < 2) *reinterpret_cast<float2*>(wsum + warp * 4 + 2 * lane) = make_float2(l0, l1);
        stsm4t(sb + OFF_PALL + as * 2112 + (i8 & 3) * 528 + (32 * warp + 8 * j8) * 2,
               pack_bf16(p[0][0], p[0][1]), pack_bf16(p[0][2], p[0][3]),
               pack_bf16(p[1][0], p[1][1]), pack_bf16(p[1][2], p[1][3]));
        asm volatile("fence.proxy.async.shared::cta;" ::: "memory");
        csync();
        if (warp == 0) {
            if (lane < 16) {
                const int head = lane & 3, dst = lane >> 2;
                float l = 0.f, m = -INFINITY;
#pragma unroll
                for (int w = 0; w < 8; w++) { l += wsum[w * 4 + head]; m = fmaxf(m, wmax[w * 4 + head]); }
                const uint32_t a = sb + OFF_SBUF + (as * 4 + head) * 8;
                if (dst == as) *reinterpret_cast<float2*>(smem + OFF_SBUF + (as * 4 + head) * 8) = make_float2(m, l);
                else st_async2(mapa(a, (rk & 4) + dst), m, l, mapa(bar0 + 8 * B_P, (rk & 4) + dst));
            } else if (lane < 20) {
                const int dst = lane - 16;
                if (dst != as) {
                    const uint32_t a = sb + OFF_PALL + as * 2112;
                    bulk_s2dsm(mapa(a, (rk & 4) + dst), a, 2112, mapa(bar0 + 8 * B_P, (rk & 4) + dst));
                }
            }
            __syncwarp();
        }
    }
    TS(6);
    if (warp == 4 || warp == 5) activation();
    csync();
    mbar_wait_cluster(bar0 + 8 * B_P);
    TS(17);

    {
        const int sp = warp >> 1, mt = warp & 1;
        float wgt[2];
        {
            const float2* sb2 = reinterpret_cast<const float2*>(smem + OFF_SBUF);
            const float gb = gate_s[ab];
#pragma unroll
            for (int e = 0; e < 2; e++) {
                const float2 s0 = sb2[bp + e], s1 = sb2[4 + bp + e], s2 = sb2[8 + bp + e], s3 = sb2[12 + bp + e];
                const float mm = fmaxf(fmaxf(s0.x, s1.x), fmaxf(s2.x, s3.x));
                const float e0 = exp2f((s0.x - mm) * SC), e1 = exp2f((s1.x - mm) * SC), e2 = exp2f((s2.x - mm) * SC), e3 = exp2f((s3.x - mm) * SC);
                const float l = (e0 * s0.y + e1 * s1.y) + (e2 * s2.y + e3 * s3.y);
                wgt[e] = (sp == 0 ? e0 : sp == 1 ? e1 : sp == 2 ? e2 : e3) * gb / l;
            }
        }
        float o0[4] = {}, o1[4] = {};
#pragma unroll
        for (int c = 0; c < 8; c++) {
            uint32_t pf[4];
            ldsm4(pf, sb + OFF_PALL + sp * 2112 + (i8 & 3) * 528 + (32 * c + 8 * j8) * 2);
            const int j = C_V + c;
            wait_full(j);
#pragma unroll
            for (int ks = 0; ks < 2; ks++) {
                const int row = 16 * ks + i8 + 8 * (j8 >> 1);
                uint32_t a[4];
                ldsm4t(a, slot(j) + sp * 2048 + addr64(row, 2 * mt + (j8 & 1)));
                if (ks & 1) mma16816(o1, a, pf[2], pf[3]);
                else        mma16816(o0, a, pf[0], pf[1]);
            }
            if (j + NSLOT < NCHUNK) { __syncwarp(); if (lane == 0) mbar_arrive_n(empty_bar(j), 1); }
        }
        TS(18);
        float* oc = reinterpret_cast<float*>(smem + OFF_RED);
        const int d = 16 * mt + g + 8 * hi;
        oc[(sp * 4 + bp) * 32 + d] = wgt[0] * (hi ? o0[2] + o1[2] : o0[0] + o1[0]);
        oc[(sp * 4 + bp + 1) * 32 + d] = wgt[1] * (hi ? o0[3] + o1[3] : o0[1] + o1[1]);
        csync();
        if (tid < 128) st_mail(o_slot, tagw((oc[tid] + oc[128 + tid]) + (oc[256 + tid] + oc[384 + tid]), tag));
    }
    TS(7);

    if (warp < 4) {
        wait_full(C_TAIL + O_AFTER);
        uint4 v[4];
        poll_mail<4>(v, g_o + (warp * HQ + 4 * rk) * DH + 4 * lane, DH, tag);
        TS(20);
#pragma unroll
        for (int i = 0; i < 4; i++)
            *reinterpret_cast<uint2*>(smem + OFF_XS + warp * 1040 + (128 * i + 4 * lane) * 2) =
                make_uint2(pack_bf16(u2f(v[i].x), u2f(v[i].y)), pack_bf16(u2f(v[i].z), u2f(v[i].w)));
        TS(8);
        asm volatile("bar.arrive 4, 256;" ::: "memory");

        if (warp == 0) {
            mbar_wait_cluster(bar0 + 8 * B_OUT);
            TS(10);
            const float4* pb = reinterpret_cast<const float4*>(smem + OFF_PBUF);
            const float4 p0 = pb[lane], p1 = pb[32 + lane], p2 = pb[64 + lane], p3 = pb[96 + lane];
            const float s0 = (p0.x + p1.x) + (p2.x + p3.x), s1 = (p0.y + p1.y) + (p2.y + p3.y);
            const float s2 = (p0.z + p1.z) + (p2.z + p3.z), s3 = (p0.w + p1.w) + (p2.w + p3.w);
            const bool up16 = lane & 16, up8 = lane & 8;
            float a0 = up16 ? s2 : s0, a1 = up16 ? s3 : s1;
            const float b0 = up16 ? s0 : s2, b1 = up16 ? s1 : s3;
            a0 += __shfl_xor_sync(0xffffffffu, b0, 16);
            a1 += __shfl_xor_sync(0xffffffffu, b1, 16);
            float c0 = up8 ? a1 : a0;
            const float d0 = up8 ? a0 : a1;
            c0 += __shfl_xor_sync(0xffffffffu, d0, 8);
            c0 += __shfl_xor_sync(0xffffffffu, c0, 4);
            if (!(lane & 4)) prm.out[(lane >> 3) * D_MODEL + 32 * cl + 4 * rk + (lane & 3)] = __float2bfloat16(c0);
            if (lane == 0) g_epoch[cta * 32] = epoch + 1;
            TS(11);
        }
    } else {
        const int q = warp - 4;
        auto act_gather = [&]() {
            uint4 v[2];
            const int u0 = 32 * q + lane;
            const float* pa = g_a + (224 * rk + u0) * 4;
            poll_mail<2>(v, pa, q < 3 ? 512 : 0, tag);
            __nv_bfloat16* as_ = reinterpret_cast<__nv_bfloat16*>(smem + OFF_AS);
            as_[u0] = __float2bfloat16(u2f(v[0].x)); as_[232 + u0] = __float2bfloat16(u2f(v[0].y));
            as_[464 + u0] = __float2bfloat16(u2f(v[0].z)); as_[696 + u0] = __float2bfloat16(u2f(v[0].w));
            if (q < 3) {
                as_[128 + u0] = __float2bfloat16(u2f(v[1].x)); as_[232 + 128 + u0] = __float2bfloat16(u2f(v[1].y));
                as_[464 + 128 + u0] = __float2bfloat16(u2f(v[1].z)); as_[696 + 128 + u0] = __float2bfloat16(u2f(v[1].w));
            }
            TS(19);
        };
        act_gather();
        const int arow = 32 * q + i8 + 8 * (j8 >> 1);
        float acc[2][2][4] = {};
        auto w2_part = [&]() {
#pragma unroll
            for (int c = 0; c < 2; c++) {
                if (c == 0 || q < 3) {
                    uint32_t af[4];
                    ldsm4(af, sb + OFF_AS + (i8 & 3) * 464 + (128 * c + 32 * q + 8 * j8) * 2);
                    wait_full(C_W2 + c);
#pragma unroll
                    for (int ks = 0; ks < 2; ks++)
#pragma unroll
                        for (int mt = 0; mt < 2; mt++) {
                            uint32_t a[4];
                            ldsm4t(a, slot(C_W2 + c) + addr64(arow + 16 * ks, 2 * mt + (j8 & 1)));
                            mma16816(acc[mt][ks], a, af[2 * ks], af[2 * ks + 1]);
                        }
                }
            }
        };
        constexpr int NPRE = 4;
        uint32_t aw[4][2][2][4];
#pragma unroll
        for (int c = 0; c < NPRE; c++) {
            wait_full(C_WO + c);
#pragma unroll
            for (int ks = 0; ks < 2; ks++)
#pragma unroll
                for (int mt = 0; mt < 2; mt++)
                    ldsm4t(aw[c][ks][mt], slot(C_WO + c) + addr64(arow + 16 * ks, 2 * mt + (j8 & 1)));
        }
        TS(13);
        asm volatile("bar.sync 4, 256;" ::: "memory");
#pragma unroll
        for (int c = 0; c < 4; c++) {
            uint32_t of[4];
            ldsm4(of, sb + OFF_XS + (i8 & 3) * 1040 + (128 * c + 32 * q + 8 * j8) * 2);
            if (c >= NPRE) {
                wait_full(C_WO + c);
#pragma unroll
                for (int ks = 0; ks < 2; ks++)
#pragma unroll
                    for (int mt = 0; mt < 2; mt++)
                        ldsm4t(aw[c][ks][mt], slot(C_WO + c) + addr64(arow + 16 * ks, 2 * mt + (j8 & 1)));
            }
#pragma unroll
            for (int ks = 0; ks < 2; ks++)
#pragma unroll
                for (int mt = 0; mt < 2; mt++) mma16816(acc[mt][ks], aw[c][ks][mt], of[2 * ks], of[2 * ks + 1]);
        }
        TS(14);
        w2_part();
        TS(9);
#pragma unroll
        for (int mt = 0; mt < 2; mt++) {
            const int col = 16 * mt + g + 8 * hi, owner = col >> 2;
            st_async2(mapa(sb + OFF_PBUF + ((rk * 4 + q) * 16 + (col & 3) * 4 + bp) * 4, owner),
                      hi ? acc[mt][0][2] + acc[mt][1][2] : acc[mt][0][0] + acc[mt][1][0],
                      hi ? acc[mt][0][3] + acc[mt][1][3] : acc[mt][0][1] + acc[mt][1][1],
                      mapa(bar0 + 8 * B_OUT, owner));
        }
        TS(16);
    }
    TS_DUMP();
}

typedef CUresult (*EncodeTiledFn)(CUtensorMap*, CUtensorMapDataType, cuuint32_t, void*, const cuuint64_t*,
                                  const cuuint64_t*, const cuuint32_t*, const cuuint32_t*, CUtensorMapInterleave,
                                  CUtensorMapSwizzle, CUtensorMapL2promotion, CUtensorMapFloatOOBfill);

#define L2PROMO CU_TENSOR_MAP_L2_PROMOTION_L2_128B

void encode(EncodeTiledFn fn, CUtensorMap* m, const void* base, int rank, const cuuint64_t* dims, const cuuint64_t* strides,
            const cuuint32_t* box, CUtensorMapSwizzle sw) {
    const cuuint32_t es[4] = {1, 1, 1, 1};
    fn(m, CU_TENSOR_MAP_DATA_TYPE_BFLOAT16, rank, const_cast<void*>(base), dims, strides, box, es,
       CU_TENSOR_MAP_INTERLEAVE_NONE, sw, L2PROMO, CU_TENSOR_MAP_FLOAT_OOB_FILL_NONE);
}
void encode2d(EncodeTiledFn fn, CUtensorMap* m, const void* base, uint64_t cols, uint64_t rows,
              uint32_t boxc, uint32_t boxr, CUtensorMapSwizzle sw) {
    const cuuint64_t dims[2] = {cols, rows}, str[1] = {cols * 2};
    const cuuint32_t box[2] = {boxc, boxr};
    encode(fn, m, base, 2, dims, str, box, sw);
}

}

extern "C" void kernel_launch(void* const* d_in, const int* in_sizes, int n_in, void* d_out, int out_size) {
    (void)in_sizes; (void)n_in; (void)out_size;
    static EncodeTiledFn fn = nullptr;
    static float* scratch = nullptr;
    if (!fn) {
        void* p = nullptr;
        cudaDriverEntryPointQueryResult st;
        cudaGetDriverEntryPoint("cuTensorMapEncodeTiled", &p, cudaEnableDefault, &st);
        fn = reinterpret_cast<EncodeTiledFn>(p);
        cudaFuncSetAttribute(gated_mix_kernel, cudaFuncAttributeMaxDynamicSharedMemorySize, SMEM_BYTES);
        void* sp = nullptr;
        cudaGetSymbolAddress(&sp, g_scratch);
        scratch = static_cast<float*>(sp);
    }
    Params prm;
    prm.x = static_cast<const __nv_bfloat16*>(d_in[0]);
    prm.b1 = static_cast<const __nv_bfloat16*>(d_in[7]);
    prm.gate_w = static_cast<const __nv_bfloat16*>(d_in[9]);
    prm.out = static_cast<__nv_bfloat16*>(d_out);
    prm.wq = static_cast<const char*>(d_in[3]);
    prm.scratch = scratch;
    encode2d(fn, &prm.m_wq, d_in[3], HQ * DH, D_MODEL, 32, 128, CU_TENSOR_MAP_SWIZZLE_64B);
    encode2d(fn, &prm.m_w1, d_in[6], FF, D_MODEL, 64, 64, CU_TENSOR_MAP_SWIZZLE_128B);
    {
        const cuuint64_t dims[3] = {64, (cuuint64_t)4 * HKV * SK, 2}, str[2] = {DH * 2, 128};
        const cuuint32_t box[3] = {64, 32, 2};
        encode(fn, &prm.m_k, d_in[1], 3, dims, str, box, CU_TENSOR_MAP_SWIZZLE_128B);
    }
    {
        const cuuint64_t dims[4] = {DH, 256, 4, 4 * HKV}, str[3] = {DH * 2, 256 * DH * 2, (cuuint64_t)SK * DH * 2};
        const cuuint32_t box[4] = {32, 32, 4, 1};
        encode(fn, &prm.m_v, static_cast<const char*>(d_in[2]) + (size_t)(SK - WIN) * DH * 2, 4, dims, str, box, CU_TENSOR_MAP_SWIZZLE_64B);
    }
    encode2d(fn, &prm.m_wo, d_in[4], D_MODEL, HQ * DH, 32, 128, CU_TENSOR_MAP_SWIZZLE_64B);
    encode2d(fn, &prm.m_w2, d_in[8], D_MODEL, FF, 32, 128, CU_TENSOR_MAP_SWIZZLE_64B);
    gated_mix_kernel<<<NCTA, NTHREADS, SMEM_BYTES, cudaStreamPerThread>>>(prm);
}
```

```cpp
#include <cuda_runtime.h>
#include <cuda_bf16.h>
#include <cuda.h>
#include <stdint.h>

namespace {

constexpr int NCTA = 128;
constexpr int NTHREADS = 288;

constexpr int PACE_T0 = 500, PACE_NS = 355, WINDOW = 7;
constexpr int Q_AFTER_K = 1;
constexpr int O_AFTER_WO = 1;

constexpr int D_MODEL = 512, HQ = 32, HKV = 8, SK = 4096, WIN = 1024, DH = 128, FF = 1792;

constexpr int C_WQ = 0, C_W1 = 4, C_K = 6, C_V = 14, C_WO = 22, C_W2 = 26, NCHUNK = 28;
constexpr int NSLOT = 11;
constexpr int OFF_XS = NSLOT * 8192;
constexpr int OFF_RED = OFF_XS + 4 * 1040;
constexpr int OFF_PALL = OFF_RED + 4096;
constexpr int OFF_QS = OFF_PALL + 4 * 2112;
constexpr int OFF_AS = OFF_QS + 4 * 272;
constexpr int OFF_HBUF = OFF_AS + 4 * 464;
constexpr int OFF_SBUF = OFF_HBUF + 1792;
constexpr int OFF_PBUF = OFF_SBUF + 128;
constexpr int OFF_WMAX = OFF_PBUF + 2048;
constexpr int OFF_WSUM = OFF_WMAX + 128;
constexpr int OFF_GATE = OFF_WSUM + 128;
constexpr int OFF_EPOCH = OFF_GATE + 16;
constexpr int OFF_BAR = OFF_EPOCH + 16;
constexpr int B_EMPTY = NSLOT, B_H = 2 * NSLOT, B_P = B_H + 1, B_OUT = B_H + 2, NBAR = B_H + 3;
constexpr int SMEM_BYTES = OFF_BAR + NBAR * 8;
static_assert(OFF_BAR % 8 == 0 && OFF_PALL % 16 == 0 && OFF_PBUF % 16 == 0 && OFF_QS % 16 == 0 && OFF_AS % 16 == 0, "align");
static_assert(SMEM_BYTES <= 115712, "two CTAs must fit on one SM so that all 16 clusters are co-resident");

struct alignas(64) Params {
    const __nv_bfloat16* x;
    const __nv_bfloat16* b1;
    const __nv_bfloat16* gate_w;
    __nv_bfloat16* out;
    const char* wq;
    float* scratch;
    alignas(64) CUtensorMap m_wq;
    alignas(64) CUtensorMap m_w1;
    alignas(64) CUtensorMap m_k;
    alignas(64) CUtensorMap m_v;
    alignas(64) CUtensorMap m_wo;
    alignas(64) CUtensorMap m_w2;
};

constexpr int SC_EPOCH = 0;
constexpr int SC_Q = SC_EPOCH + NCTA * 32;
constexpr int SC_A = SC_Q + 4 * HQ * DH;
constexpr int SC_O = SC_A + FF * 4;
constexpr int SC_TOTAL = SC_O + 4 * HQ * DH;
__device__ __align__(128) float g_scratch[SC_TOTAL];

__device__ __forceinline__ uint32_t smem_u32(const void* p) { return (uint32_t)__cvta_generic_to_shared(p); }
__device__ __forceinline__ void mbar_init(uint32_t bar, uint32_t cnt) {
    asm volatile("mbarrier.init.shared::cta.b64 [%0], %1;" :: "r"(bar), "r"(cnt) : "memory");
}
__device__ __forceinline__ void mbar_expect_tx(uint32_t bar, uint32_t bytes) {
    asm volatile("mbarrier.arrive.expect_tx.shared::cta.b64 _, [%0], %1;" :: "r"(bar), "r"(bytes) : "memory");
}
__device__ __forceinline__ void mbar_arrive_n(uint32_t bar, uint32_t n) {
    asm volatile("mbarrier.arrive.shared::cta.b64 _, [%0], %1;" :: "r"(bar), "r"(n) : "memory");
}
__device__ __forceinline__ bool mbar_try(uint32_t bar, uint32_t parity) {
    uint32_t ok;
    asm volatile("{\n.reg .pred p;\nmbarrier.try_wait.parity.shared::cta.b64 p, [%1], %2;\nselp.u32 %0, 1, 0, p;\n}"
                 : "=r"(ok) : "r"(bar), "r"(parity) : "memory");
    return ok;
}
__device__ __forceinline__ bool mbar_try_cluster(uint32_t bar) {
    uint32_t ok;
    asm volatile("{\n.reg .pred p;\nmbarrier.try_wait.parity.acquire.cluster.shared::cta.b64 p, [%1], 0;\nselp.u32 %0, 1, 0, p;\n}"
                 : "=r"(ok) : "r"(bar) : "memory");
    return ok;
}
constexpr int SPIN_LIMIT = 1 << 20;
__device__ __forceinline__ void mbar_wait(uint32_t bar, uint32_t parity) {
    int it = 0;
    while (!mbar_try(bar, parity)) { if (++it > SPIN_LIMIT) __trap(); }
}
__device__ __forceinline__ void mbar_wait_cluster(uint32_t bar) {
    int it = 0;
    while (!mbar_try_cluster(bar)) { if (++it > SPIN_LIMIT) __trap(); }
    __syncwarp();
}
__device__ __forceinline__ void tma2d(uint32_t dst, const CUtensorMap* m, int c0, int c1, uint32_t bar, uint64_t pol) {
    asm volatile("cp.async.bulk.tensor.2d.shared::cluster.global.mbarrier::complete_tx::bytes.L2::cache_hint"
                 " [%0], [%1, {%3, %4}], [%2], %5;"
                 :: "r"(dst), "l"(m), "r"(bar), "r"(c0), "r"(c1), "l"(pol) : "memory");
}
__device__ __forceinline__ void tma3d(uint32_t dst, const CUtensorMap* m, int c0, int c1, int c2, uint32_t bar, uint64_t pol) {
    asm volatile("cp.async.bulk.tensor.3d.shared::cluster.global.mbarrier::complete_tx::bytes.L2::cache_hint"
                 " [%0], [%1, {%3, %4, %5}], [%2], %6;"
                 :: "r"(dst), "l"(m), "r"(bar), "r"(c0), "r"(c1), "r"(c2), "l"(pol) : "memory");
}
__device__ __forceinline__ void tma4d(uint32_t dst, const CUtensorMap* m, int c0, int c1, int c2, int c3, uint32_t bar, uint64_t pol) {
    asm volatile("cp.async.bulk.tensor.4d.shared::cluster.global.mbarrier::complete_tx::bytes.L2::cache_hint"
                 " [%0], [%1, {%3, %4, %5, %6}], [%2], %7;"
                 :: "r"(dst), "l"(m), "r"(bar), "r"(c0), "r"(c1), "r"(c2), "r"(c3), "l"(pol) : "memory");
}
__device__ __forceinline__ uint32_t mapa(uint32_t a, uint32_t rank) {
    uint32_t d;
    asm("mapa.shared::cluster.u32 %0, %1, %2;" : "=r"(d) : "r"(a), "r"(rank));
    return d;
}
__device__ __forceinline__ void st_async2(uint32_t addr, float a, float b, uint32_t bar) {
    asm volatile("st.async.weak.shared::cluster.mbarrier::complete_tx::bytes.v2.f32 [%0], {%1, %2}, [%3];"
                 :: "r"(addr), "f"(a), "f"(b), "r"(bar) : "memory");
}
__device__ __forceinline__ void bulk_s2dsm(uint32_t dst, uint32_t src, uint32_t bytes, uint32_t bar) {
    asm volatile("cp.async.bulk.shared::cluster.shared::cta.mbarrier::complete_tx::bytes [%0], [%1], %2, [%3];"
                 :: "r"(dst), "r"(src), "r"(bytes), "r"(bar) : "memory");
}
__device__ __forceinline__ void ldsm4(uint32_t (&r)[4], uint32_t a) {
    asm volatile("ldmatrix.sync.aligned.m8n8.x4.shared.b16 {%0,%1,%2,%3}, [%4];"
                 : "=r"(r[0]), "=r"(r[1]), "=r"(r[2]), "=r"(r[3]) : "r"(a) : "memory");
}
__device__ __forceinline__ void ldsm4t(uint32_t (&r)[4], uint32_t a) {
    asm volatile("ldmatrix.sync.aligned.m8n8.x4.trans.shared.b16 {%0,%1,%2,%3}, [%4];"
                 : "=r"(r[0]), "=r"(r[1]), "=r"(r[2]), "=r"(r[3]) : "r"(a) : "memory");
}
__device__ __forceinline__ void stsm4t(uint32_t a, uint32_t r0, uint32_t r1, uint32_t r2, uint32_t r3) {
    asm volatile("stmatrix.sync.aligned.m8n8.x4.trans.shared.b16 [%0], {%1,%2,%3,%4};"
                 :: "r"(a), "r"(r0), "r"(r1), "r"(r2), "r"(r3) : "memory");
}
__device__ __forceinline__ void mma16816(float (&c)[4], const uint32_t (&a)[4], uint32_t b0, uint32_t b1) {
    asm volatile("mma.sync.aligned.m16n8k16.row.col.f32.bf16.bf16.f32 {%0,%1,%2,%3}, {%4,%5,%6,%7}, {%8,%9}, {%0,%1,%2,%3};"
                 : "+f"(c[0]), "+f"(c[1]), "+f"(c[2]), "+f"(c[3])
                 : "r"(a[0]), "r"(a[1]), "r"(a[2]), "r"(a[3]), "r"(b0), "r"(b1));
}
__device__ __forceinline__ uint32_t pack_bf16(float lo, float hi) {
    uint32_t r;
    asm("cvt.rn.bf16x2.f32 %0, %1, %2;" : "=r"(r) : "f"(hi), "f"(lo));
    return r;
}
#define PIN32(x) asm volatile("" : "+r"(x))
#define PIN64(x) asm volatile("" : "+l"(x))
__device__ __forceinline__ void csync() { asm volatile("bar.sync 1, 256;" ::: "memory"); }

__device__ __forceinline__ uint32_t tagw(float v, uint32_t tag) { return (__float_as_uint(v) & ~3u) | tag; }
__device__ __forceinline__ void st_mail(float* p, uint32_t v) {
    asm volatile("st.relaxed.gpu.global.b32 [%0], %1;" :: "l"(p), "r"(v) : "memory");
}
__device__ __forceinline__ uint4 ld_mail4(const float* p) {
    uint4 v;
    asm volatile("ld.relaxed.gpu.global.v4.b32 {%0,%1,%2,%3}, [%4];" : "=r"(v.x), "=r"(v.y), "=r"(v.z), "=r"(v.w) : "l"(p) : "memory");
    return v;
}
__device__ __forceinline__ bool tag_ok(const uint4& v, uint32_t tag) {
    return (((v.x ^ tag) | (v.y ^ tag) | (v.z ^ tag) | (v.w ^ tag)) & 3u) == 0;
}
template <int N>
__device__ __forceinline__ void poll_mail(uint4 (&v)[N], const float* p, int stride, uint32_t tag) {
    bool ok[N];
#pragma unroll
    for (int i = 0; i < N; i++) ok[i] = false;
    int it = 0;
    while (true) {
#pragma unroll
        for (int i = 0; i < N; i++) if (!ok[i]) v[i] = ld_mail4(p + i * stride);
        bool all = true;
#pragma unroll
        for (int i = 0; i < N; i++) { if (!ok[i]) ok[i] = __all_sync(0xffffffffu, tag_ok(v[i], tag)); all = all && ok[i]; }
        if (all) break;
        if (++it > SPIN_LIMIT) __trap();
    }
}
__device__ __forceinline__ float u2f(uint32_t u) { return __uint_as_float(u); }
__device__ __forceinline__ uint64_t gtime() { uint64_t t; asm volatile("mov.u64 %0, %globaltimer;" : "=l"(t)); return t; }
__device__ __forceinline__ float mish(float h) {
    const float e = __expf(fminf(h, 30.f));
    const float n = e * (e + 2.f);
    return h * __fdividef(n, n + 2.f);
}
__device__ __forceinline__ uint32_t addr64(int row, int chunk16) { return row * 64 + ((chunk16 ^ ((row >> 1) & 3)) << 4); }

__global__ void __cluster_dims__(8, 1, 1) __launch_bounds__(NTHREADS, 2)
gated_mix_kernel(const __grid_constant__ Params prm) {
    extern __shared__ __align__(1024) unsigned char smem[];
    const uint32_t sb = smem_u32(smem);
    const int warp = threadIdx.x >> 5, lane = threadIdx.x & 31;
    const int cta = blockIdx.x;
    const int cl = cta >> 3, rk = cta & 7;
    const int clo = (2 * (cl & 7) + (cl >> 3) + 1) & 15;
    const uint32_t bar0 = sb + OFF_BAR;
    auto full_bar = [&](int j) { return bar0 + 8 * (j % NSLOT); };
    auto empty_bar = [&](int j) { return bar0 + 8 * (B_EMPTY + j % NSLOT); };
    auto slot = [&](int j) { return sb + (j % NSLOT) * 8192; };
    auto wait_full = [&](int j) { mbar_wait(full_bar(j), (j / NSLOT) & 1); __syncwarp(); };
    if (threadIdx.x == 0)
        asm volatile("cp.async.bulk.prefetch.L2.global [%0], %1;" :: "l"(prm.wq + (size_t)cta * 32768), "r"(32768) : "memory");

    if (warp == 8) {
        const uint64_t t0 = gtime() + PACE_T0;
        uint64_t pol;
        asm volatile("createpolicy.fractional.L2::evict_first.b64 %0, 1.0;" : "=l"(pol));
        const int pair = cta >> 2, sp = cta & 3;
        const int krow = pair * SK + (SK - WIN) + sp * 256;
        auto issue = [&](int j) {
            const uint32_t bar = full_bar(j), dst = slot(j);
            mbar_expect_tx(bar, 8192);
            if (j < 4)                               tma2d(dst, &prm.m_wq, cta * 32, j * 128, bar, pol);
            else if (j >= C_W1 && j < C_W1 + 2)      tma2d(dst, &prm.m_w1, cl * 112 + (j - C_W1) * 64, rk * 64, bar, pol);
            else if (j >= C_K && j < C_K + 8)        tma3d(dst, &prm.m_k, 0, krow + (j - C_K) * 32, 0, bar, pol);
            else if (j >= C_V && j < C_V + 8)        tma4d(dst, &prm.m_v, sp * 32, (j - C_V) * 32, 0, pair, bar, pol);
            else if (j >= C_WO && j < C_WO + 4)      tma2d(dst, &prm.m_wo, clo * 32, rk * 512 + (j - C_WO) * 128, bar, pol);
            else                                     tma2d(dst, &prm.m_w2, clo * 32, rk * 224 + (j - C_W2) * 128, bar, pol);
        };
        if (lane == 0) {
#pragma unroll
            for (int j = 0; j < 4; j++) { mbar_init(full_bar(j), 1); issue(j); }
            asm volatile("prefetch.tensormap [%0];" :: "l"(&prm.m_w1) : "memory");
            asm volatile("prefetch.tensormap [%0];" :: "l"(&prm.m_k) : "memory");
        }
        __syncwarp();
        asm volatile("bar.sync 2, 288;" ::: "memory");
        asm volatile("barrier.cluster.arrive.relaxed.aligned;" ::: "memory");
        if (lane == 0) {
            asm volatile("prefetch.tensormap [%0];" :: "l"(&prm.m_v) : "memory");
            asm volatile("prefetch.tensormap [%0];" :: "l"(&prm.m_wo) : "memory");
            asm volatile("prefetch.tensormap [%0];" :: "l"(&prm.m_w2) : "memory");
#pragma unroll
            for (int j = 4; j < NCHUNK; j++) {
                if (j >= WINDOW) mbar_wait(full_bar(j - WINDOW), ((j - WINDOW) / NSLOT) & 1);
                if (j >= NSLOT) mbar_wait(empty_bar(j), ((j - NSLOT) / NSLOT) & 1);
                {
                    const long long due = (long long)(j - 4) * PACE_NS;
                    int it = 0;
                    while ((long long)(gtime() - t0) < due && ++it < SPIN_LIMIT) {}
                }
                issue(j);
            }
        }
        return;
    }

    const int g = lane >> 2, t = lane & 3;
    const int j8 = lane >> 3, i8 = lane & 7;
    const int hi = t >> 1, bp = 2 * (t & 1);
    const int tid = threadIdx.x;
    float* const g_q = prm.scratch + SC_Q;
    float* const g_a = prm.scratch + SC_A;
    float* const g_o = prm.scratch + SC_O;
    unsigned int* const g_epoch = reinterpret_cast<unsigned int*>(prm.scratch) + SC_EPOCH;
    const int ab = cta >> 5, ahkv = (cta >> 2) & 7, as = cta & 3;

    uint4 xv0, xv1;
    unsigned int epoch = 0;
    float* const q_slot = g_q + ((tid & 3) * HQ + (cta >> 2)) * DH + 32 * (cta & 3) + ((tid >> 2) & 31);
    if (warp < 4) {
        xv0 = __ldg(reinterpret_cast<const uint4*>(prm.x) + tid);
        xv1 = __ldg(reinterpret_cast<const uint4*>(prm.x) + 128 + tid);
        if (tid == 0) asm volatile("ld.relaxed.gpu.global.u32 %0, [%1];" : "=r"(epoch) : "l"(&g_epoch[cta * 32]) : "memory");
        st_mail(q_slot, 0u);
    } else {
        if (lane == 0) {
            if (warp == 4) {
#pragma unroll
                for (int b = 4; b < 10; b++) mbar_init(bar0 + 8 * b, 1);
            } else if (warp == 5) {
                mbar_init(bar0 + 8 * 10, 1);
#pragma unroll
                for (int b = 0; b < 4; b++) mbar_init(bar0 + 8 * (B_EMPTY + b), 8);
            } else if (warp == 6) {
#pragma unroll
                for (int b = 4; b < 9; b++) mbar_init(bar0 + 8 * (B_EMPTY + b), 8);
            } else {
                mbar_init(bar0 + 8 * (B_EMPTY + 9), 8);
                mbar_init(bar0 + 8 * (B_EMPTY + 10), 8);
                mbar_init(bar0 + 8 * B_H, 1);   mbar_expect_tx(bar0 + 8 * B_H, 1792);
                mbar_init(bar0 + 8 * B_P, 1);   mbar_expect_tx(bar0 + 8 * B_P, 3 * (2112 + 32));
                mbar_init(bar0 + 8 * B_OUT, 1); mbar_expect_tx(bar0 + 8 * B_OUT, 2048);
            }
            asm volatile("fence.mbarrier_init.release.cluster;" ::: "memory");
        }
        __syncwarp();
    }
    asm volatile("bar.sync 2, 288;" ::: "memory");
    asm volatile("barrier.cluster.arrive.relaxed.aligned;" ::: "memory");
    if (warp < 4) {
        *reinterpret_cast<uint4*>(smem + OFF_XS + (tid >> 6) * 1040 + (tid & 63) * 16) = xv0;
        *reinterpret_cast<uint4*>(smem + OFF_XS + (2 + (tid >> 6)) * 1040 + (tid & 63) * 16) = xv1;
    }
    csync();
    uint32_t xq[2][4];
#pragma unroll
    for (int u = 0; u < 2; u++) ldsm4(xq[u], sb + OFF_XS + (i8 & 3) * 1040 + (64 * warp + 32 * u + 8 * j8) * 2);
    uint32_t tag;

    {
        float aq[2][4] = {};
        const int j = C_WQ + (warp >> 1);
        wait_full(j);
#pragma unroll
        for (int ks = 0; ks < 4; ks++) {
            const int row = 64 * (warp & 1) + 16 * ks + i8 + 8 * (j8 >> 1);
#pragma unroll
            for (int mt = 0; mt < 2; mt++) {
                uint32_t a[4];
                ldsm4t(a, slot(j) + addr64(row, 2 * mt + (j8 & 1)));
                mma16816(aq[mt], a, xq[ks >> 1][2 * (ks & 1)], xq[ks >> 1][2 * (ks & 1) + 1]);
            }
        }
        __syncwarp();
        if (lane == 0) mbar_arrive_n(empty_bar(j), 4);
        float* redq = reinterpret_cast<float*>(smem + OFF_RED);
        {
            const float v0 = hi ? aq[1][0] : aq[0][0], v1 = hi ? aq[1][1] : aq[0][1];
            const float v2 = hi ? aq[1][2] : aq[0][2], v3 = hi ? aq[1][3] : aq[0][3];
            *reinterpret_cast<float2*>(redq + (warp * 32 + 16 * hi + g) * 4 + bp) = make_float2(v0, v1);
            *reinterpret_cast<float2*>(redq + (warp * 32 + 16 * hi + g + 8) * 4 + bp) = make_float2(v2, v3);
        }
        if (tid == 0) *reinterpret_cast<unsigned int*>(smem + OFF_EPOCH) = epoch;
        csync();
        epoch = *reinterpret_cast<const unsigned int*>(smem + OFF_EPOCH);
        tag = 1u + (epoch & 1u);
        if (tid == 0) g_epoch[cta * 32] = epoch + 1;
        if (tid < 128) {
            float s = 0.f;
#pragma unroll
            for (int w = 0; w < 8; w++) s += redq[w * 128 + tid];
            st_mail(q_slot, (pack_bf16(0.f, s) & 0xffff0000u) | tag);
        }
    }

    float* const o_slot = g_o + (ab * HQ + 4 * ahkv + (tid >> 5)) * DH + 32 * as + (tid & 31);
    float* const a_slot = g_a + (112 * cl + 14 * rk) * 4 + (tid - 128);
    if (tid < 128) st_mail(o_slot, 0u);
    else if (tid < 128 + 56) st_mail(a_slot, 0u);
    asm volatile("barrier.cluster.wait.aligned;" ::: "memory");

    uint32_t xh[2][4];
    if (warp >= 4) {
#pragma unroll
        for (int u = 0; u < 2; u++) ldsm4(xh[u], sb + OFF_XS + (i8 & 3) * 1040 + (64 * rk + 32 * u + 8 * j8) * 2);
    }
    auto h_partial = [&](const uint32_t (&xf)[2][4]) {
        const int b = warp - 4;
        const int j = C_W1 + (b >> 1);
        wait_full(j);
        float h[2][4] = {};
#pragma unroll
        for (int ks = 0; ks < 4; ks++) {
            const int row = 16 * ks + i8 + 8 * (j8 >> 1);
#pragma unroll
            for (int m = 0; m < 2; m++) {
                uint32_t a[4];
                ldsm4t(a, slot(j) + row * 128 + (((4 * (b & 1) + 2 * m + (j8 & 1)) ^ (row & 7)) << 4));
                mma16816(h[m], a, xf[ks >> 1][2 * (ks & 1)], xf[ks >> 1][2 * (ks & 1) + 1]);
            }
        }
        __syncwarp();
        if (lane == 0) mbar_arrive_n(empty_bar(j), 4);
#pragma unroll
        for (int m = 0; m < 2; m++) {
            const int u = 16 * (2 * b + m) + g + 8 * hi;
            if (u < 112) {
                const int owner = u / 14, ul = u - 14 * owner;
                st_async2(mapa(sb + OFF_HBUF + ((rk * 14 + ul) * 4 + bp) * 4, owner),
                          hi ? h[m][2] : h[m][0], hi ? h[m][3] : h[m][1], mapa(bar0 + 8 * B_H, owner));
            }
        }
    };
    const float* gate_s = reinterpret_cast<const float*>(smem + OFF_GATE);
    auto activation = [&]() {
        const int tt = tid - 128;
        const float bias = tt < 56 ? __bfloat162float(prm.b1[112 * cl + 14 * rk + (tt >> 2)]) : 0.f;
        mbar_wait_cluster(bar0 + 8 * B_H);
        if (tt < 56) {
            const float* hb = reinterpret_cast<const float*>(smem + OFF_HBUF);
            float h = bias;
#pragma unroll
            for (int src = 0; src < 8; src++) h += hb[src * 56 + tt];
            st_mail(a_slot, tagw(mish(h) * (1.f - gate_s[tt & 3]), tag));
        }
        __syncwarp();
    };

    if (warp < 4) {
        wait_full(C_K + Q_AFTER_K);
        uint4 v[1];
        poll_mail<1>(v, g_q + (ab * HQ + 4 * ahkv + warp) * DH + 4 * lane, 0, tag);
        const uint32_t p0 = (v[0].x >> 16) | (v[0].y & 0xffff0000u), p1 = (v[0].z >> 16) | (v[0].w & 0xffff0000u);
        *reinterpret_cast<uint2*>(smem + OFF_QS + warp * 272 + lane * 8) = make_uint2(p0, p1);
    } else {
        const int b = warp - 4;
        const uint4* gr = reinterpret_cast<const uint4*>(prm.gate_w);
        const uint4 gv0 = __ldg(gr + lane), gv1 = __ldg(gr + 32 + lane);
        h_partial(xh);
        float s = 0.f;
#pragma unroll
        for (int u = 0; u < 2; u++) {
            const uint4 xx = *reinterpret_cast<const uint4*>(smem + OFF_XS + b * 1040 + (u * 32 + lane) * 16), gv = u ? gv1 : gv0;
            const uint32_t xa[4] = {xx.x, xx.y, xx.z, xx.w}, ga[4] = {gv.x, gv.y, gv.z, gv.w};
#pragma unroll
            for (int e = 0; e < 4; e++) {
                s = fmaf(u2f(xa[e] << 16), u2f(ga[e] << 16), s);
                s = fmaf(u2f(xa[e] & 0xffff0000u), u2f(ga[e] & 0xffff0000u), s);
            }
        }
#pragma unroll
        for (int o = 16; o > 0; o >>= 1) s += __shfl_xor_sync(0xffffffffu, s, o);
        if (lane == 0) reinterpret_cast<float*>(smem + OFF_GATE)[b] = 1.f / (1.f + __expf(-s));
    }
    csync();

    constexpr float SC = 0.08838834764831845f * 1.4426950408889634f;
    float* wmax = reinterpret_cast<float*>(smem + OFF_WMAX);
    float* wsum = reinterpret_cast<float*>(smem + OFF_WSUM);
    {
        uint32_t qf[4][4];
#pragma unroll
        for (int u = 0; u < 4; u++) ldsm4(qf[u], sb + OFF_QS + (i8 & 3) * 272 + (32 * u + 8 * j8) * 2);
        float s[2][4] = {};
        const int j = C_K + warp;
        wait_full(j);
#pragma unroll
        for (int ks = 0; ks < 8; ks++) {
#pragma unroll
            for (int mt = 0; mt < 2; mt++) {
                const int row = 16 * mt + i8 + 8 * (j8 & 1);
                uint32_t a[4];
                ldsm4(a, slot(j) + (ks >> 2) * 4096 + row * 128 + (((2 * (ks & 3) + (j8 >> 1)) ^ (row & 7)) << 4));
                mma16816(s[mt], a, qf[ks >> 1][2 * (ks & 1)], qf[ks >> 1][2 * (ks & 1) + 1]);
            }
        }
        __syncwarp();
        if (lane == 0) mbar_arrive_n(empty_bar(j), 8);
        float m0 = fmaxf(fmaxf(s[0][0], s[0][2]), fmaxf(s[1][0], s[1][2]));
        float m1 = fmaxf(fmaxf(s[0][1], s[0][3]), fmaxf(s[1][1], s[1][3]));
#pragma unroll
        for (int o = 4; o < 32; o <<= 1) {
            m0 = fmaxf(m0, __shfl_xor_sync(0xffffffffu, m0, o));
            m1 = fmaxf(m1, __shfl_xor_sync(0xffffffffu, m1, o));
        }
        if (lane < 2) *reinterpret_cast<float2*>(wmax + warp * 4 + 2 * lane) = make_float2(m0, m1);
        csync();
        m0 = -INFINITY; m1 = -INFINITY;
#pragma unroll
        for (int w = 0; w < 8; w++) {
            const float2 mm = *reinterpret_cast<const float2*>(wmax + w * 4 + bp);
            m0 = fmaxf(m0, mm.x); m1 = fmaxf(m1, mm.y);
        }
        float p[2][4];
#pragma unroll
        for (int mt = 0; mt < 2; mt++) {
            p[mt][0] = exp2f((s[mt][0] - m0) * SC); p[mt][1] = exp2f((s[mt][1] - m1) * SC);
            p[mt][2] = exp2f((s[mt][2] - m0) * SC); p[mt][3] = exp2f((s[mt][3] - m1) * SC);
        }
        float l0 = (p[0][0] + p[0][2]) + (p[1][0] + p[1][2]), l1 = (p[0][1] + p[0][3]) + (p[1][1] + p[1][3]);
#pragma unroll
        for (int o = 4; o < 32; o <<= 1) {
            l0 += __shfl_xor_sync(0xffffffffu, l0, o);
            l1 += __shfl_xor_sync(0xffffffffu, l1, o);
        }
        if (lane < 2) *reinterpret_cast<float2*>(wsum + warp * 4 + 2 * lane) = make_float2(l0, l1);
        stsm4t(sb + OFF_PALL + as * 2112 + (i8 & 3) * 528 + (32 * warp + 8 * j8) * 2,
               pack_bf16(p[0][0], p[0][1]), pack_bf16(p[0][2], p[0][3]),
               pack_bf16(p[1][0], p[1][1]), pack_bf16(p[1][2], p[1][3]));
        asm volatile("fence.proxy.async.shared::cta;" ::: "memory");
        csync();
        if (warp == 0) {
            if (lane < 16) {
                const int head = lane & 3, dst = lane >> 2;
                float l = 0.f, m = -INFINITY;
#pragma unroll
                for (int w = 0; w < 8; w++) { l += wsum[w * 4 + head]; m = fmaxf(m, wmax[w * 4 + head]); }
                const uint32_t a = sb + OFF_SBUF + (as * 4 + head) * 8;
                if (dst == as) *reinterpret_cast<float2*>(smem + OFF_SBUF + (as * 4 + head) * 8) = make_float2(m, l);
                else st_async2(mapa(a, (rk & 4) + dst), m, l, mapa(bar0 + 8 * B_P, (rk & 4) + dst));
            } else if (lane < 20) {
                const int dst = lane - 16;
                if (dst != as) {
                    const uint32_t a = sb + OFF_PALL + as * 2112;
                    bulk_s2dsm(mapa(a, (rk & 4) + dst), a, 2112, mapa(bar0 + 8 * B_P, (rk & 4) + dst));
                }
            }
            __syncwarp();
        }
    }
    if (warp == 4 || warp == 5) activation();
    csync();
    mbar_wait_cluster(bar0 + 8 * B_P);
    {
        const int sp = warp >> 1, mt = warp & 1;
        float wgt[2];
        {
            const float2* sb2 = reinterpret_cast<const float2*>(smem + OFF_SBUF);
            const float gb = gate_s[ab];
#pragma unroll
            for (int e = 0; e < 2; e++) {
                const float2 s0 = sb2[bp + e], s1 = sb2[4 + bp + e], s2 = sb2[8 + bp + e], s3 = sb2[12 + bp + e];
                const float mm = fmaxf(fmaxf(s0.x, s1.x), fmaxf(s2.x, s3.x));
                const float e0 = exp2f((s0.x - mm) * SC), e1 = exp2f((s1.x - mm) * SC), e2 = exp2f((s2.x - mm) * SC), e3 = exp2f((s3.x - mm) * SC);
                const float l = (e0 * s0.y + e1 * s1.y) + (e2 * s2.y + e3 * s3.y);
                wgt[e] = (sp == 0 ? e0 : sp == 1 ? e1 : sp == 2 ? e2 : e3) * gb / l;
            }
        }
        uint32_t oc_st = sb + OFF_RED + ((sp * 4 + bp) * 32 + 16 * mt + g + 8 * hi) * 4, oc_ld = sb + OFF_RED + (tid & 127) * 4;
        float* o_dst = o_slot;
        PIN32(oc_st); PIN32(oc_ld); PIN64(o_dst);
        float o0[4] = {}, o1[4] = {};
#pragma unroll
        for (int c = 0; c < 8; c++) {
            uint32_t pf[4];
            ldsm4(pf, sb + OFF_PALL + sp * 2112 + (i8 & 3) * 528 + (32 * c + 8 * j8) * 2);
            const int j = C_V + c;
            wait_full(j);
#pragma unroll
            for (int ks = 0; ks < 2; ks++) {
                const int row = 16 * ks + i8 + 8 * (j8 >> 1);
                uint32_t a[4];
                ldsm4t(a, slot(j) + sp * 2048 + addr64(row, 2 * mt + (j8 & 1)));
                if (ks & 1) mma16816(o1, a, pf[2], pf[3]);
                else        mma16816(o0, a, pf[0], pf[1]);
            }
            if (j + NSLOT < NCHUNK) { __syncwarp(); if (lane == 0) mbar_arrive_n(empty_bar(j), 1); }
        }
        asm volatile("st.shared.f32 [%0], %1;" :: "r"(oc_st), "f"(wgt[0] * (hi ? o0[2] + o1[2] : o0[0] + o1[0])) : "memory");
        asm volatile("st.shared.f32 [%0+128], %1;" :: "r"(oc_st), "f"(wgt[1] * (hi ? o0[3] + o1[3] : o0[1] + o1[1])) : "memory");
        csync();
        if (tid < 128) {
            float c0, c1, c2, c3;
            asm volatile("ld.shared.f32 %0, [%1];" : "=f"(c0) : "r"(oc_ld) : "memory");
            asm volatile("ld.shared.f32 %0, [%1+512];" : "=f"(c1) : "r"(oc_ld) : "memory");
            asm volatile("ld.shared.f32 %0, [%1+1024];" : "=f"(c2) : "r"(oc_ld) : "memory");
            asm volatile("ld.shared.f32 %0, [%1+1536];" : "=f"(c3) : "r"(oc_ld) : "memory");
            st_mail(o_dst, tagw((c0 + c1) + (c2 + c3), tag));
        }
    }
    if (warp < 4) {
        wait_full(C_WO + O_AFTER_WO);
        uint4 v[4];
        poll_mail<4>(v, g_o + (warp * HQ + 4 * rk) * DH + 4 * lane, DH, tag);
#pragma unroll
        for (int i = 0; i < 4; i++)
            *reinterpret_cast<uint2*>(smem + OFF_XS + warp * 1040 + (128 * i + 4 * lane) * 2) =
                make_uint2(pack_bf16(u2f(v[i].x), u2f(v[i].y)), pack_bf16(u2f(v[i].z), u2f(v[i].w)));
        asm volatile("bar.arrive 4, 256;" ::: "memory");

        if (warp == 0) {
            __nv_bfloat16* optr = prm.out + (lane >> 3) * D_MODEL + 32 * clo + 4 * rk + (lane & 3);
            PIN64(optr);
            mbar_wait_cluster(bar0 + 8 * B_OUT);
            const float4* pb = reinterpret_cast<const float4*>(smem + OFF_PBUF);
            const float4 p0 = pb[lane], p1 = pb[32 + lane], p2 = pb[64 + lane], p3 = pb[96 + lane];
            const float s0 = (p0.x + p1.x) + (p2.x + p3.x), s1 = (p0.y + p1.y) + (p2.y + p3.y);
            const float s2 = (p0.z + p1.z) + (p2.z + p3.z), s3 = (p0.w + p1.w) + (p2.w + p3.w);
            const bool up16 = lane & 16, up8 = lane & 8;
            float a0 = up16 ? s2 : s0, a1 = up16 ? s3 : s1;
            const float b0 = up16 ? s0 : s2, b1 = up16 ? s1 : s3;
            a0 += __shfl_xor_sync(0xffffffffu, b0, 16);
            a1 += __shfl_xor_sync(0xffffffffu, b1, 16);
            float c0 = up8 ? a1 : a0;
            const float d0 = up8 ? a0 : a1;
            c0 += __shfl_xor_sync(0xffffffffu, d0, 8);
            c0 += __shfl_xor_sync(0xffffffffu, c0, 4);
            if (!(lane & 4)) *optr = __float2bfloat16(c0);
        }
    } else {
        const int q = warp - 4;
        auto act_gather = [&]() {
            uint4 v[2];
            const int u0 = 32 * q + lane;
            const float* pa = g_a + (224 * rk + u0) * 4;
            poll_mail<2>(v, pa, q < 3 ? 512 : 0, tag);
            __nv_bfloat16* as_ = reinterpret_cast<__nv_bfloat16*>(smem + OFF_AS);
            as_[u0] = __float2bfloat16(u2f(v[0].x)); as_[232 + u0] = __float2bfloat16(u2f(v[0].y));
            as_[464 + u0] = __float2bfloat16(u2f(v[0].z)); as_[696 + u0] = __float2bfloat16(u2f(v[0].w));
            if (q < 3) {
                as_[128 + u0] = __float2bfloat16(u2f(v[1].x)); as_[232 + 128 + u0] = __float2bfloat16(u2f(v[1].y));
                as_[464 + 128 + u0] = __float2bfloat16(u2f(v[1].z)); as_[696 + 128 + u0] = __float2bfloat16(u2f(v[1].w));
            }
        };
        act_gather();
        const int arow = 32 * q + i8 + 8 * (j8 >> 1);
        uint32_t pdst[2], pbar[2];
#pragma unroll
        for (int mt = 0; mt < 2; mt++) {
            const int col = 16 * mt + g + 8 * hi, owner = col >> 2;
            pdst[mt] = mapa(sb + OFF_PBUF + ((rk * 4 + q) * 16 + (col & 3) * 4 + bp) * 4, owner);
            pbar[mt] = mapa(bar0 + 8 * B_OUT, owner);
            PIN32(pdst[mt]); PIN32(pbar[mt]);
        }
        float acc[2][2][4] = {};
        auto w2_part = [&]() {
#pragma unroll
            for (int c = 0; c < 2; c++) {
                if (c == 0 || q < 3) {
                    uint32_t af[4];
                    ldsm4(af, sb + OFF_AS + (i8 & 3) * 464 + (128 * c + 32 * q + 8 * j8) * 2);
                    wait_full(C_W2 + c);
#pragma unroll
                    for (int ks = 0; ks < 2; ks++) {
#pragma unroll
                        for (int mt = 0; mt < 2; mt++) {
                            uint32_t a[4];
                            ldsm4t(a, slot(C_W2 + c) + addr64(arow + 16 * ks, 2 * mt + (j8 & 1)));
                            mma16816(acc[mt][ks], a, af[2 * ks], af[2 * ks + 1]);
                        }
                    }
                }
            }
        };
        uint32_t aw[4][2][2][4];
#pragma unroll
        for (int c = 0; c < 4; c++) {
            wait_full(C_WO + c);
#pragma unroll
            for (int ks = 0; ks < 2; ks++)
#pragma unroll
                for (int mt = 0; mt < 2; mt++)
                    ldsm4t(aw[c][ks][mt], slot(C_WO + c) + addr64(arow + 16 * ks, 2 * mt + (j8 & 1)));
        }
        asm volatile("bar.sync 4, 256;" ::: "memory");
#pragma unroll
        for (int c = 0; c < 4; c++) {
            uint32_t of[4];
            ldsm4(of, sb + OFF_XS + (i8 & 3) * 1040 + (128 * c + 32 * q + 8 * j8) * 2);
#pragma unroll
            for (int ks = 0; ks < 2; ks++)
#pragma unroll
                for (int mt = 0; mt < 2; mt++) mma16816(acc[mt][ks], aw[c][ks][mt], of[2 * ks], of[2 * ks + 1]);
        }
        w2_part();
#pragma unroll
        for (int mt = 0; mt < 2; mt++) {
            st_async2(pdst[mt],
                      hi ? acc[mt][0][2] + acc[mt][1][2] : acc[mt][0][0] + acc[mt][1][0],
                      hi ? acc[mt][0][3] + acc[mt][1][3] : acc[mt][0][1] + acc[mt][1][1],
                      pbar[mt]);
        }
    }
}

typedef CUresult (*EncodeTiledFn)(CUtensorMap*, CUtensorMapDataType, cuuint32_t, void*, const cuuint64_t*,
                                  const cuuint64_t*, const cuuint32_t*, const cuuint32_t*, CUtensorMapInterleave,
                                  CUtensorMapSwizzle, CUtensorMapL2promotion, CUtensorMapFloatOOBfill);

void encode(EncodeTiledFn fn, CUtensorMap* m, const void* base, int rank, const cuuint64_t* dims, const cuuint64_t* strides,
            const cuuint32_t* box, CUtensorMapSwizzle sw) {
    const cuuint32_t es[4] = {1, 1, 1, 1};
    fn(m, CU_TENSOR_MAP_DATA_TYPE_BFLOAT16, rank, const_cast<void*>(base), dims, strides, box, es,
       CU_TENSOR_MAP_INTERLEAVE_NONE, sw, CU_TENSOR_MAP_L2_PROMOTION_L2_128B, CU_TENSOR_MAP_FLOAT_OOB_FILL_NONE);
}
void encode2d(EncodeTiledFn fn, CUtensorMap* m, const void* base, uint64_t cols, uint64_t rows,
              uint32_t boxc, uint32_t boxr, CUtensorMapSwizzle sw) {
    const cuuint64_t dims[2] = {cols, rows}, str[1] = {cols * 2};
    const cuuint32_t box[2] = {boxc, boxr};
    encode(fn, m, base, 2, dims, str, box, sw);
}

}

extern "C" void kernel_launch(void* const* d_in, const int* in_sizes, int n_in, void* d_out, int out_size) {
    (void)in_sizes; (void)n_in; (void)out_size;
    static EncodeTiledFn fn = nullptr;
    static float* scratch = nullptr;
    if (!fn) {
        void* p = nullptr;
        cudaDriverEntryPointQueryResult st;
        cudaGetDriverEntryPoint("cuTensorMapEncodeTiled", &p, cudaEnableDefault, &st);
        fn = reinterpret_cast<EncodeTiledFn>(p);
        cudaFuncSetAttribute(gated_mix_kernel, cudaFuncAttributeMaxDynamicSharedMemorySize, SMEM_BYTES);
        cudaFuncSetAttribute(gated_mix_kernel, cudaFuncAttributePreferredSharedMemoryCarveout, cudaSharedmemCarveoutMaxShared);
        void* sp = nullptr;
        cudaGetSymbolAddress(&sp, g_scratch);
        scratch = static_cast<float*>(sp);
    }
    Params prm;
    prm.x = static_cast<const __nv_bfloat16*>(d_in[0]);
    prm.b1 = static_cast<const __nv_bfloat16*>(d_in[7]);
    prm.gate_w = static_cast<const __nv_bfloat16*>(d_in[9]);
    prm.out = static_cast<__nv_bfloat16*>(d_out);
    prm.wq = static_cast<const char*>(d_in[3]);
    prm.scratch = scratch;
    encode2d(fn, &prm.m_wq, d_in[3], HQ * DH, D_MODEL, 32, 128, CU_TENSOR_MAP_SWIZZLE_64B);
    encode2d(fn, &prm.m_w1, d_in[6], FF, D_MODEL, 64, 64, CU_TENSOR_MAP_SWIZZLE_128B);
    {
        const cuuint64_t dims[3] = {64, (cuuint64_t)4 * HKV * SK, 2}, str[2] = {DH * 2, 128};
        const cuuint32_t box[3] = {64, 32, 2};
        encode(fn, &prm.m_k, d_in[1], 3, dims, str, box, CU_TENSOR_MAP_SWIZZLE_128B);
    }
    {
        const cuuint64_t dims[4] = {DH, 256, 4, 4 * HKV}, str[3] = {DH * 2, 256 * DH * 2, (cuuint64_t)SK * DH * 2};
        const cuuint32_t box[4] = {32, 32, 4, 1};
        encode(fn, &prm.m_v, static_cast<const char*>(d_in[2]) + (size_t)(SK - WIN) * DH * 2, 4, dims, str, box, CU_TENSOR_MAP_SWIZZLE_64B);
    }
    encode2d(fn, &prm.m_wo, d_in[4], D_MODEL, HQ * DH, 32, 128, CU_TENSOR_MAP_SWIZZLE_64B);
    encode2d(fn, &prm.m_w2, d_in[8], D_MODEL, FF, 32, 128, CU_TENSOR_MAP_SWIZZLE_64B);
    gated_mix_kernel<<<NCTA, NTHREADS, SMEM_BYTES, cudaStreamPerThread>>>(prm);
}
```
